```python
import torch

def _softmax(x, axis=-1):
    return torch.softmax(x, dim=axis)
def _gelu(x):
    return torch.nn.functional.gelu(x, approximate="tanh")
def _silu(x):
    return torch.nn.functional.silu(x)
def _sigmoid(x):
    return torch.sigmoid(x)
def _layernorm(x, axis=-1, eps=1e-5):
    m = x.mean(dim=axis, keepdim=True)
    v = x.var(dim=axis, keepdim=True, unbiased=False)
    return (x - m) / torch.sqrt(v + eps)
def _scatter_add(tgt, idx, src, axis=0):
    return tgt.clone().index_add_(axis, idx, src)
def _segment_sum(src, seg, n):
    out = torch.zeros((n,) + src.shape[1:], dtype=src.dtype)
    return out.index_add_(0, seg, src)
def _pad(x, pw):
    flat = tuple(v for pair in reversed(pw) for v in pair)
    return torch.nn.functional.pad(x, flat)

kernel_name = 'parallel_sum__softmax_full_mha__dense_activation_gelu__prompt'

def setup_inputs():

    _w = (lambda a: (lambda t: t.to(torch.bfloat16) if t.is_floating_point() else t)(torch.as_tensor(a)))
    def _A_setup():
        B, S, D = 1, 2048, 576
        return {
            "x": _w((lambda *s: torch.randn(*s, dtype=torch.bfloat16) * 0.05)(B, S, D)),
            "wqkv": _w((lambda *s: torch.randn(*s, dtype=torch.bfloat16) * 0.05)(D, 3 * D)),
            "wo": _w((lambda *s: torch.randn(*s, dtype=torch.bfloat16) * 0.05)(D, D)),
        }
    _A_in = _A_setup()

    def _B_setup():
        B, S, D, F = 1, 2048, 576, 4608
        return {
            "x": _w((lambda *s: torch.randn(*s, dtype=torch.bfloat16) * 0.05)(B, S, D)),
            "w1": _w((lambda *s: torch.randn(*s, dtype=torch.bfloat16) * 0.8)(D, F) * (D ** -0.5)),
            "b1": _w((lambda *s: torch.randn(*s, dtype=torch.bfloat16) * 12.8)(F) * 0.01),
            "w2": _w((lambda *s: torch.randn(*s, dtype=torch.bfloat16) * 0.8)(F, D) * (F ** -0.5)),
            "b2": _w((lambda *s: torch.randn(*s, dtype=torch.bfloat16) * 12.8)(D) * 0.01),
        }
    _B_in = _B_setup()

    return {
        "A_x": _A_in["x"],
        "A_wqkv": _A_in["wqkv"],
        "A_wo": _A_in["wo"],
        "B_x": _B_in["x"],
        "B_w1": _B_in["w1"],
        "B_b1": _B_in["b1"],
        "B_w2": _B_in["w2"],
        "B_b2": _B_in["b2"],
    }

def reference(A_x, A_wqkv, A_wo, B_x, B_w1, B_b1, B_w2, B_b2):
    def _A_ref(x, wqkv, wo):
        B, S, D = x.shape
        H = 32; Dh = D // H
        qkv = (lambda x, *d: x.permute(*d))((x @ wqkv).reshape(B, S, 3, H, Dh), 2, 0, 3, 1, 4)
        q, k, v = qkv[0], qkv[1], qkv[2]
        scale = Dh ** -0.5
        scores = torch.einsum("bhqd,bhkd->bhqk", q, k) * scale
        p = _softmax(scores, axis=-1)
        o = torch.einsum("bhqk,bhkd->bhqd", p, v)
        return (lambda x, *d: x.permute(*d))(o, 0, 2, 1, 3).reshape(B, S, D) @ wo

    def _B_ref(x, w1, b1, w2, b2):
        h = torch.einsum("bsd,df->bsf", x, w1) + b1
        h = _gelu(h)
        return torch.einsum("bsf,fd->bsd", h, w2) + b2

    x = A_x
    xn = _layernorm(x, axis=-1)
    return x + _A_ref(xn, A_wqkv, A_wo) + _B_ref(xn, B_w1, B_b1, B_w2, B_b2)
```

```cpp
#include <cuda_runtime.h>
#include <cuda_bf16.h>
#include <cuda.h>
#include <stdint.h>

namespace {

constexpr int SEQ = 2048, DM = 576, FF = 4608, NH = 32;
constexpr int NCTA = 132, NTHREADS = 512;
constexpr uint32_t POLYMASK = 0xAD6Bu;

constexpr uint32_t SB = 0x400;
constexpr uint32_t A_OFF = SB;
constexpr uint32_t B_OFF = SB + 9 * 16384;
constexpr uint32_t KV_OFF = SB;
constexpr uint32_t BAR_OFF = B_OFF + 6 * 12288;
constexpr uint32_t BAR_FULLA = BAR_OFF, BAR_EMPTYA = BAR_FULLA + 72, BAR_FULLB = BAR_EMPTYA + 72, BAR_EMPTYB = BAR_FULLB + 48,
                   BAR_FULLKV = BAR_EMPTYB + 48, BAR_EMPTYKV = BAR_FULLKV + 64, BAR_INFO = BAR_EMPTYKV + 64;
constexpr uint32_t INFO_OFF = BAR_OFF + 512;
constexpr uint32_t ROWS_OFF = INFO_OFF + 5 * 1536;
constexpr uint32_t SMEM_END = ROWS_OFF + 1024;
constexpr uint32_t SMEM_BYTES = SMEM_END - SB;
static_assert(SMEM_BYTES <= 232448, "smem");

__device__ __align__(1024) __nv_bfloat16 g_h[SEQ * FF];
__device__ __align__(1024) __nv_bfloat16 g_o[SEQ * DM];
__device__ __align__(1024) uint8_t g_q[NH * 256 * 384];
__device__ __align__(1024) uint8_t g_kv[NH * 256 * 768];
__device__ __align__(16) float2 g_colinfo[6336];
__device__ __align__(16) float2 g_rowstat[SEQ];
__device__ float g_bound[9 * 64];
__device__ unsigned g_done;
__device__ unsigned g_prep;
__device__ unsigned g_qkv[9];
__device__ unsigned g_hflag[16 * 72];
__device__ unsigned g_oflag[32 * 32];
#define TS(i)

struct Params {
    CUtensorMap x, wqkv, w1, w1n, h, o, w2, wo;
    const __nv_bfloat16* xp; const __nv_bfloat16* wqkvp; const __nv_bfloat16* w1p; const __nv_bfloat16* b1p; const __nv_bfloat16* b2p;
    __nv_bfloat16* out;
};

template<int SD> __device__ __forceinline__ void mma_n192_ss(float* d, uint64_t da, uint64_t db) {
    asm volatile("wgmma.mma_async.sync.aligned.m64n192k16.f32.bf16.bf16 {%0,%1,%2,%3,%4,%5,%6,%7,%8,%9,%10,%11,%12,%13,%14,%15,%16,%17,%18,%19,%20,%21,%22,%23,%24,%25,%26,%27,%28,%29,%30,%31,%32,%33,%34,%35,%36,%37,%38,%39,%40,%41,%42,%43,%44,%45,%46,%47,%48,%49,%50,%51,%52,%53,%54,%55,%56,%57,%58,%59,%60,%61,%62,%63,%64,%65,%66,%67,%68,%69,%70,%71,%72,%73,%74,%75,%76,%77,%78,%79,%80,%81,%82,%83,%84,%85,%86,%87,%88,%89,%90,%91,%92,%93,%94,%95}, %96, %97, %98, 1, 1, 0, 1;\n"
      : "+f"(d[0]),"+f"(d[1]),"+f"(d[2]),"+f"(d[3]),"+f"(d[4]),"+f"(d[5]),"+f"(d[6]),"+f"(d[7]),"+f"(d[8]),"+f"(d[9]),"+f"(d[10]),"+f"(d[11]),"+f"(d[12]),"+f"(d[13]),"+f"(d[14]),"+f"(d[15]),"+f"(d[16]),"+f"(d[17]),"+f"(d[18]),"+f"(d[19]),"+f"(d[20]),"+f"(d[21]),"+f"(d[22]),"+f"(d[23]),"+f"(d[24]),"+f"(d[25]),"+f"(d[26]),"+f"(d[27]),"+f"(d[28]),"+f"(d[29]),"+f"(d[30]),"+f"(d[31]),"+f"(d[32]),"+f"(d[33]),"+f"(d[34]),"+f"(d[35]),"+f"(d[36]),"+f"(d[37]),"+f"(d[38]),"+f"(d[39]),"+f"(d[40]),"+f"(d[41]),"+f"(d[42]),"+f"(d[43]),"+f"(d[44]),"+f"(d[45]),"+f"(d[46]),"+f"(d[47]),"+f"(d[48]),"+f"(d[49]),"+f"(d[50]),"+f"(d[51]),"+f"(d[52]),"+f"(d[53]),"+f"(d[54]),"+f"(d[55]),"+f"(d[56]),"+f"(d[57]),"+f"(d[58]),"+f"(d[59]),"+f"(d[60]),"+f"(d[61]),"+f"(d[62]),"+f"(d[63]),"+f"(d[64]),"+f"(d[65]),"+f"(d[66]),"+f"(d[67]),"+f"(d[68]),"+f"(d[69]),"+f"(d[70]),"+f"(d[71]),"+f"(d[72]),"+f"(d[73]),"+f"(d[74]),"+f"(d[75]),"+f"(d[76]),"+f"(d[77]),"+f"(d[78]),"+f"(d[79]),"+f"(d[80]),"+f"(d[81]),"+f"(d[82]),"+f"(d[83]),"+f"(d[84]),"+f"(d[85]),"+f"(d[86]),"+f"(d[87]),"+f"(d[88]),"+f"(d[89]),"+f"(d[90]),"+f"(d[91]),"+f"(d[92]),"+f"(d[93]),"+f"(d[94]),"+f"(d[95])
      : "l"(da), "l"(db), "n"(SD));
}
template<int SD> __device__ __forceinline__ void mma_n64_ss(float* d, uint64_t da, uint64_t db) {
    asm volatile("wgmma.mma_async.sync.aligned.m64n64k16.f32.bf16.bf16 {%0,%1,%2,%3,%4,%5,%6,%7,%8,%9,%10,%11,%12,%13,%14,%15,%16,%17,%18,%19,%20,%21,%22,%23,%24,%25,%26,%27,%28,%29,%30,%31}, %32, %33, %34, 1, 1, 0, 1;\n"
      : "+f"(d[0]),"+f"(d[1]),"+f"(d[2]),"+f"(d[3]),"+f"(d[4]),"+f"(d[5]),"+f"(d[6]),"+f"(d[7]),"+f"(d[8]),"+f"(d[9]),"+f"(d[10]),"+f"(d[11]),"+f"(d[12]),"+f"(d[13]),"+f"(d[14]),"+f"(d[15]),"+f"(d[16]),"+f"(d[17]),"+f"(d[18]),"+f"(d[19]),"+f"(d[20]),"+f"(d[21]),"+f"(d[22]),"+f"(d[23]),"+f"(d[24]),"+f"(d[25]),"+f"(d[26]),"+f"(d[27]),"+f"(d[28]),"+f"(d[29]),"+f"(d[30]),"+f"(d[31])
      : "l"(da), "l"(db), "n"(SD));
}
template<int SD> __device__ __forceinline__ void mma_n64_rs(float* d, uint32_t a0, uint32_t a1, uint32_t a2, uint32_t a3, uint64_t db) {
    asm volatile("wgmma.mma_async.sync.aligned.m64n64k16.f32.bf16.bf16 {%0,%1,%2,%3,%4,%5,%6,%7,%8,%9,%10,%11,%12,%13,%14,%15,%16,%17,%18,%19,%20,%21,%22,%23,%24,%25,%26,%27,%28,%29,%30,%31}, {%32,%33,%34,%35}, %36, %37, 1, 1, 0;\n"
      : "+f"(d[0]),"+f"(d[1]),"+f"(d[2]),"+f"(d[3]),"+f"(d[4]),"+f"(d[5]),"+f"(d[6]),"+f"(d[7]),"+f"(d[8]),"+f"(d[9]),"+f"(d[10]),"+f"(d[11]),"+f"(d[12]),"+f"(d[13]),"+f"(d[14]),"+f"(d[15]),"+f"(d[16]),"+f"(d[17]),"+f"(d[18]),"+f"(d[19]),"+f"(d[20]),"+f"(d[21]),"+f"(d[22]),"+f"(d[23]),"+f"(d[24]),"+f"(d[25]),"+f"(d[26]),"+f"(d[27]),"+f"(d[28]),"+f"(d[29]),"+f"(d[30]),"+f"(d[31])
      : "r"(a0), "r"(a1), "r"(a2), "r"(a3), "l"(db), "n"(SD));
}
template<int SD> __device__ __forceinline__ void mma_n24_rs(float* d, uint32_t a0, uint32_t a1, uint32_t a2, uint32_t a3, uint64_t db) {
    asm volatile("wgmma.mma_async.sync.aligned.m64n24k16.f32.bf16.bf16 {%0,%1,%2,%3,%4,%5,%6,%7,%8,%9,%10,%11}, {%12,%13,%14,%15}, %16, %17, 1, 1, 1;\n"
      : "+f"(d[0]),"+f"(d[1]),"+f"(d[2]),"+f"(d[3]),"+f"(d[4]),"+f"(d[5]),"+f"(d[6]),"+f"(d[7]),"+f"(d[8]),"+f"(d[9]),"+f"(d[10]),"+f"(d[11])
      : "r"(a0), "r"(a1), "r"(a2), "r"(a3), "l"(db), "n"(SD));
}

__host__ __device__ constexpr uint64_t mkdesc(uint32_t addr, uint32_t lbo, uint32_t sbo, uint32_t swz) {
    return (uint64_t)((addr & 0x3FFFF) >> 4) | ((uint64_t)(lbo >> 4) << 16) | ((uint64_t)(sbo >> 4) << 32) | ((uint64_t)swz << 62);
}
#define WG_FENCE() asm volatile("wgmma.fence.sync.aligned;" ::: "memory")
#define WG_COMMIT() asm volatile("wgmma.commit_group.sync.aligned;" ::: "memory")
#define WG_WAIT(n) asm volatile("wgmma.wait_group.sync.aligned " #n ";" ::: "memory")
template<int N> __device__ __forceinline__ void keep(float* r) {
#pragma unroll
    for (int i = 0; i < N; i++) asm volatile("" : "+f"(r[i]) :: "memory");
}
template<int N> __device__ __forceinline__ void keep(uint32_t* r) {
#pragma unroll
    for (int i = 0; i < N; i++) asm volatile("" : "+r"(r[i]) :: "memory");
}
__device__ __forceinline__ void mbar_init(uint32_t a, uint32_t c) { asm volatile("mbarrier.init.shared::cta.b64 [%0], %1;" :: "r"(a), "r"(c) : "memory"); }
__device__ __forceinline__ void mbar_expect(uint32_t a, uint32_t b) { asm volatile("mbarrier.arrive.expect_tx.shared::cta.b64 _, [%0], %1;" :: "r"(a), "r"(b) : "memory"); }
__device__ __forceinline__ void mbar_arrive(uint32_t a) { asm volatile("mbarrier.arrive.shared::cta.b64 _, [%0];" :: "r"(a) : "memory"); }
__device__ __forceinline__ void mbar_arrive2(uint32_t a) { asm volatile("mbarrier.arrive.shared::cta.b64 _, [%0], 2;" :: "r"(a) : "memory"); }
__device__ __forceinline__ void mbar_wait(uint32_t a, uint32_t ph) {
    asm volatile("{\n.reg .pred p, q;\n.reg .u32 n;\nmov.u32 n, 0;\n"
        "LW:\nmbarrier.try_wait.parity.shared::cta.b64 p, [%0], %1;\n@p bra LD;\n"
        "add.u32 n, n, 1;\nsetp.gt.u32 q, n, 2000000;\n@q trap;\nbra LW;\nLD:\n}" :: "r"(a), "r"(ph) : "memory");
}
__device__ __forceinline__ void flag_wait(const unsigned* p, unsigned target) {
    asm volatile("{\n.reg .pred p, q;\n.reg .u32 n, v;\nmov.u32 n, 0;\n"
        "LW:\nld.acquire.gpu.global.u32 v, [%0];\nsub.u32 v, v, %1;\nsetp.ge.s32 p, v, 0;\n@p bra LD;\n"
        "nanosleep.u32 40;\nadd.u32 n, n, 1;\nsetp.gt.u32 q, n, 4000000;\n@q trap;\nbra LW;\nLD:\n}" :: "l"(p), "r"(target) : "memory");
}
__device__ __forceinline__ void red_release(unsigned* p, unsigned v) { asm volatile("red.release.gpu.global.add.u32 [%0], %1;" :: "l"(p), "r"(v) : "memory"); }
__device__ __forceinline__ void st_release(unsigned* p, unsigned v) { asm volatile("st.release.gpu.global.u32 [%0], %1;" :: "l"(p), "r"(v) : "memory"); }
__device__ __forceinline__ unsigned ld_relaxed(const unsigned* p) { unsigned v; asm volatile("ld.relaxed.gpu.global.u32 %0, [%1];" : "=r"(v) : "l"(p) : "memory"); return v; }
__device__ __forceinline__ void fence_async() { asm volatile("fence.proxy.async;" ::: "memory"); }
__device__ __forceinline__ void bar_sync(int id, int n) { asm volatile("bar.sync %0, %1;" :: "r"(id), "r"(n) : "memory"); }
__device__ __forceinline__ void bar_arrive(int id, int n) { asm volatile("bar.arrive %0, %1;" :: "r"(id), "r"(n) : "memory"); }
__device__ __forceinline__ void bulk_load(uint32_t dst, const void* src, uint32_t bytes, uint32_t bar) {
    asm volatile("cp.async.bulk.shared::cluster.global.mbarrier::complete_tx::bytes [%0], [%1], %2, [%3];" :: "r"(dst), "l"(src), "r"(bytes), "r"(bar) : "memory");
}
__device__ __forceinline__ void tma2d(uint32_t dst, const CUtensorMap* m, int c0, int c1, uint32_t bar) {
    asm volatile("cp.async.bulk.tensor.2d.shared::cluster.global.mbarrier::complete_tx::bytes [%0], [%1, {%3, %4}], [%2];"
        :: "r"(dst), "l"(m), "r"(bar), "r"(c0), "r"(c1) : "memory");
}
__device__ __forceinline__ void tma3d(uint32_t dst, const CUtensorMap* m, int c0, int c1, int c2, uint32_t bar) {
    asm volatile("cp.async.bulk.tensor.3d.shared::cluster.global.mbarrier::complete_tx::bytes [%0], [%1, {%3, %4, %5}], [%2];"
        :: "r"(dst), "l"(m), "r"(bar), "r"(c0), "r"(c1), "r"(c2) : "memory");
}
__device__ __forceinline__ void tma5d(uint32_t dst, const CUtensorMap* m, int c0, int c4, uint32_t bar) {
    asm volatile("cp.async.bulk.tensor.5d.shared::cluster.global.mbarrier::complete_tx::bytes [%0], [%1, {%3, %5, %5, %5, %4}], [%2];"
        :: "r"(dst), "l"(m), "r"(bar), "r"(c0), "r"(c4), "r"(0) : "memory");
}
__device__ __forceinline__ uint32_t pack_bf16(float lo, float hi) {
    uint32_t r; asm("cvt.rn.bf16x2.f32 %0, %1, %2;" : "=r"(r) : "f"(hi), "f"(lo)); return r;
}
__device__ __forceinline__ float bf_lo(uint32_t v) { return __uint_as_float(v << 16); }
__device__ __forceinline__ float bf_hi(uint32_t v) { return __uint_as_float(v & 0xffff0000u); }
__device__ __forceinline__ float4 lds128(uint32_t a) { float4 v; asm volatile("ld.shared.v4.f32 {%0,%1,%2,%3}, [%4];" : "=f"(v.x), "=f"(v.y), "=f"(v.z), "=f"(v.w) : "r"(a)); return v; }
__device__ __forceinline__ float2 lds64(uint32_t a) { float2 v; asm volatile("ld.shared.v2.f32 {%0,%1}, [%2];" : "=f"(v.x), "=f"(v.y) : "r"(a)); return v; }
__device__ __forceinline__ float ex2(float x) { float y; asm("ex2.approx.ftz.f32 %0, %1;" : "=f"(y) : "f"(x)); return y; }

struct Sched { int m, j, ntiles, isG, aidx; };
__device__ __forceinline__ Sched get_sched() {
    Sched s; int c = blockIdx.x;
    if (c < 128) { s.m = c >> 3; s.j = c & 7; s.isG = s.j < 3; s.ntiles = s.isG ? 5 : 4; s.aidx = 4 + s.m * 5 + (s.j - 3); }
    else { s.m = 0; s.j = 0; s.isG = 0; s.ntiles = 0; s.aidx = c - 128; }
    return s;
}
constexpr int NACTA = 84;

template<int NB>
__device__ __forceinline__ void gemm1_mainloop(float* acc0, float* acc1, int q, bool waitA, bool releaseA, bool handoff, bool elect) {
    constexpr uint64_t dA = mkdesc(A_OFF, 16, 1024, 1), dB = mkdesc(B_OFF, 4096, 1024, 1);
    const uint32_t par = (3 * q) & 1;
    if (q > 0) bar_sync(8 + (q & 1), 256);
#pragma unroll
    for (int hs = 0; hs < 18; hs++) {
        const int kb = hs >> 1, half = hs & 1, st = hs % 6;
        if (half == 0 && waitA) mbar_wait(BAR_FULLA + 8 * kb, 0);
        mbar_wait(BAR_FULLB + 8 * st, par ^ ((hs / 6) & 1));
        if (hs == 17 && handoff) bar_arrive(8 + ((q + 1) & 1), 256);
        WG_FENCE();
#pragma unroll
        for (int k = 0; k < 2; k++) {
            const uint64_t a = dA + (uint64_t)((kb * 16384 + (half * 2 + k) * 32) >> 4);
            const uint64_t b = dB + (uint64_t)((st * 12288 + k * 2048) >> 4);
            if (hs == 0 && k == 0) {
                if (NB == 24) { mma_n192_ss<0>(acc0, a, b); mma_n192_ss<0>(acc1, a + (8192 >> 4), b); }
                else { mma_n64_ss<0>(acc0, a, b); mma_n64_ss<0>(acc1, a + (8192 >> 4), b); }
            } else {
                if (NB == 24) { mma_n192_ss<1>(acc0, a, b); mma_n192_ss<1>(acc1, a + (8192 >> 4), b); }
                else { mma_n64_ss<1>(acc0, a, b); mma_n64_ss<1>(acc1, a + (8192 >> 4), b); }
            }
        }
        WG_COMMIT();
        if (hs > 0) {
            WG_WAIT(1);
            if (elect) {
                mbar_arrive2(BAR_EMPTYB + 8 * ((hs - 1) % 6));
                if (half == 0 && releaseA) mbar_arrive2(BAR_EMPTYA + 8 * (kb - 1));
            }
        }
    }
    WG_WAIT(0);
    if (elect) { mbar_arrive2(BAR_EMPTYB + 8 * 5); if (releaseA) mbar_arrive2(BAR_EMPTYA + 8 * 8); }
    keep<NB * 4>(acc0); keep<NB * 4>(acc1);
}

template<int NB>
__device__ __forceinline__ void epilogue_gelu(float* acc0, float* acc1, uint32_t info, int m, int col0, int warp, int g, int t) {
    float2 rs[4];
#pragma unroll
    for (int r = 0; r < 4; r++) rs[r] = lds64(ROWS_OFF + 8 * ((r >> 1) * 64 + warp * 16 + g + (r & 1) * 8));
    __nv_bfloat16* hp = g_h + (size_t)(m * 128 + warp * 16 + g) * FF + col0 + t * 8;
#pragma unroll
    for (int i4 = 0; i4 < NB / 4; i4++) {
        uint32_t o[4][4];
#pragma unroll
        for (int ii = 0; ii < 4; ii++) {
            const int i = i4 * 4 + ii;
            const float4 ci = lds128(info + 8 * (8 * i + 2 * t));
#pragma unroll
            for (int r = 0; r < 4; r++) {
                const float* a = (r >> 1) ? acc1 : acc0;
                float y[2];
#pragma unroll
                for (int e = 0; e < 2; e++) {
                    const float xh = fmaf(a[4 * i + (r & 1) * 2 + e], rs[r].x, fmaf(rs[r].y, e ? ci.z : ci.x, e ? ci.w : ci.y));
                    const float z = xh * fmaf(xh * xh, 0.28541927f, 1.5957691f);
                    float th; asm("tanh.approx.f32 %0, %1;" : "=f"(th) : "f"(z));
                    y[e] = fmaf(xh, th, xh);
                }
                o[r][ii] = pack_bf16(y[0], y[1]);
            }
        }
#pragma unroll
        for (int r = 0; r < 4; r++)
            *(uint4*)(hp + (size_t)((r >> 1) * 64 + (r & 1) * 8) * FF + i4 * 32) = make_uint4(o[r][0], o[r][1], o[r][2], o[r][3]);
    }
}

__device__ __forceinline__ void epilogue_qkv(float* acc0, float* acc1, uint32_t info, int m, int n, int warp, int g, int t) {
    const int which = n / 3, c0 = (n % 3) * 192 + 2 * t;
    const float sc = which == 0 ? 2.0f * 0.23570226f * 1.44269504f : 2.0f;
    float2 rs[4];
#pragma unroll
    for (int r = 0; r < 4; r++) { rs[r] = lds64(ROWS_OFF + 8 * ((r >> 1) * 64 + warp * 16 + g + (r & 1) * 8)); rs[r].x *= sc; rs[r].y *= sc; }
    const uint32_t hstride = which == 0 ? 98304u : 196608u, rstride = which == 0 ? 384u : 768u;
    uint8_t* base = (which == 0 ? g_q : g_kv + (which == 2 ? 384 : 0)) + (size_t)(m * 16 + warp * 2) * rstride + g * 16;
    float s1[4] = {0.f, 0.f, 0.f, 0.f}, s2[4] = {0.f, 0.f, 0.f, 0.f}, mx[4] = {0.f, 0.f, 0.f, 0.f};
#pragma unroll
    for (int i = 0; i < 24; i++) {
        const float4 ci = lds128(info + 8 * (8 * i + 2 * t));
        const int cc = c0 + 8 * i, head = (cc * 3641) >> 16, d = cc - head * 18;
        uint8_t* p = base + (size_t)head * hstride + (d >> 3) * 128 + (d & 7) * 2;
#pragma unroll
        for (int r = 0; r < 4; r++) {
            const float* a = (r >> 1) ? acc1 : acc0;
            const float y0 = fmaf(a[4 * i + (r & 1) * 2], rs[r].x, rs[r].y * ci.x), y1 = fmaf(a[4 * i + (r & 1) * 2 + 1], rs[r].x, rs[r].y * ci.z);
            const uint32_t v = pack_bf16(y0, y1);
            const int rgo = (r >> 1) * 8 + (r & 1);
            uint8_t* pr = p + rgo * rstride;
            if (d == 16 && which != 0) {
                uint32_t e1, e2;
                if (which == 1) { const bool poly = (POLYMASK >> ((warp * 2 + rgo) & 15)) & 1; e1 = e2 = poly ? 0x3f803f80u : 0u; }
                else { e1 = 0x00003f80u; e2 = 0u; }
                *(uint4*)pr = make_uint4(v, e1, e2, 0u);
            } else *(uint32_t*)pr = v;
            const float b = fmaf(y0, y0, y1 * y1);
            mx[r] = fmaxf(mx[r], b + s1[r] + s2[r]); s2[r] = s1[r]; s1[r] = b;
        }
    }
    float bound = 0.f;
#pragma unroll
    for (int r = 0; r < 4; r++) {
        float v = mx[r];
        v += __shfl_xor_sync(0xffffffffu, v, 1); v += __shfl_xor_sync(0xffffffffu, v, 2);
        bound = fmaxf(bound, v);
        if (!(v == v)) bound = __int_as_float(0x7f800000);
    }
#pragma unroll
    for (int o = 4; o < 32; o <<= 1) bound = fmaxf(bound, __shfl_xor_sync(0xffffffffu, bound, o));
    if (g == 0 && t == 0) g_bound[n * 64 + m * 4 + warp] = bound;
}

__device__ __forceinline__ uint32_t exp2_fma(float a, float b, uint32_t c3f00) {
    uint32_t s, m, e, r;
    asm("prmt.b32 %0, %1, %2, 0x5410;" : "=r"(s) : "r"(__float_as_uint(a)), "r"(__float_as_uint(b)));
    asm("lop3.b32 %0, %1, 0x007f007f, %2, 0xEA;" : "=r"(m) : "r"(s), "r"(c3f00));
    asm("and.b32 %0, %1, 0xff80ff80;" : "=r"(e) : "r"(s));
    asm("fma.rn.bf16x2 %0, %1, %2, %3;" : "=r"(r) : "r"(s), "r"(m), "r"(e));
    return r;
}
template<int HALF> __device__ __forceinline__ void exps(const float* S, uint32_t* P, uint32_t c3f00) {
#pragma unroll
    for (int i = 0; i < 8; i++) {
        if ((POLYMASK >> (i + 8 * HALF)) & 1) { P[2 * i] = exp2_fma(S[4 * i], S[4 * i + 1], c3f00); P[2 * i + 1] = exp2_fma(S[4 * i + 2], S[4 * i + 3], c3f00); }
        else { P[2 * i] = pack_bf16(ex2(S[4 * i]), ex2(S[4 * i + 1])); P[2 * i + 1] = pack_bf16(ex2(S[4 * i + 2]), ex2(S[4 * i + 3])); }
    }
}
__device__ __forceinline__ void pv(float* O, const uint32_t* P, uint64_t dv) {
#pragma unroll
    for (int kk = 0; kk < 4; kk++) mma_n24_rs<1>(O, P[4 * kk], P[4 * kk + 1], P[4 * kk + 2], P[4 * kk + 3], dv + kk * (1536 >> 4));
}
__device__ __forceinline__ void qk(float* S, const uint32_t* q, uint64_t dk) {
    mma_n64_rs<0>(S, q[0], q[1], q[2], q[3], dk);
    mma_n64_rs<1>(S, q[4], q[5], q[6], q[7], dk + (256 >> 4));
}
__device__ __forceinline__ void kv_refill(int sl, uint32_t par, const uint8_t* src, int lane) {
    mbar_wait(BAR_EMPTYKV + 8 * sl, par);
    if (lane == 0) {
        mbar_expect(BAR_FULLKV + 8 * sl, 24576);
        bulk_load(KV_OFF + sl * 24576, src + sl * 24576, 24576, BAR_FULLKV + 8 * sl);
    }
    __syncwarp();
}

__device__ __forceinline__ void attention(int aidx, int wg, unsigned epoch) {
    const int lane = threadIdx.x & 31, g = lane >> 2, t = lane & 3;
    const int warp = __shfl_sync(0xffffffffu, (threadIdx.x >> 5) & 3, 0);
    const bool elect = (threadIdx.x & 127) == 0;
    constexpr uint64_t dk0 = mkdesc(KV_OFF, 128, 768, 0), dv0 = mkdesc(KV_OFF + 384, 768, 128, 0);
    const uint32_t zero = (uint32_t)(aidx >> 20) * lane;
    const uint32_t c3f00 = __shfl_sync(0xffffffffu, 0x3f003f00u + zero, 0);
    if (lane < 9) flag_wait(&g_qkv[lane], (epoch + 1) * 16);
    __syncwarp();
    fence_async();
    int r = 0;
#pragma unroll 1
    for (int rd = aidx; rd < 256; rd += NACTA, r++) {
        const uint32_t ph = r & 1;
        const bool has_next = rd + NACTA < 256;
        const int head = rd >> 3, rb = (rd & 7) * 4 + wg;
        const uint8_t* src_cur = g_kv + (size_t)head * 196608;
        const uint8_t* src_next = g_kv + (size_t)((rd + NACTA) >> 3) * 196608;
        bool fast;
        {
            const int t0 = (head * 18) / 192, t1 = (head * 18 + 17) / 192;
            float b[3];
#pragma unroll
            for (int w = 0; w < 3; w++) {
                float a0 = fmaxf(__ldcg(&g_bound[(w * 3 + t0) * 64 + lane]), __ldcg(&g_bound[(w * 3 + t0) * 64 + 32 + lane]));
                float a1 = fmaxf(__ldcg(&g_bound[(w * 3 + t1) * 64 + lane]), __ldcg(&g_bound[(w * 3 + t1) * 64 + 32 + lane]));
#pragma unroll
                for (int o = 1; o < 32; o <<= 1) { a0 = fmaxf(a0, __shfl_xor_sync(0xffffffffu, a0, o)); a1 = fmaxf(a1, __shfl_xor_sync(0xffffffffu, a1, o)); }
                b[w] = t1 != t0 ? a0 + a1 : a0;
            }
            fast = (b[0] * b[1] <= 8100.0f) && (b[2] <= 1.0e9f);
        }
        const uint8_t* qp = g_q + (size_t)head * 98304 + (size_t)(rb * 8 + warp * 2) * 384 + g * 16 + t * 4;
        uint32_t q[8];
        q[0] = __ldcg((const uint32_t*)qp); q[1] = __ldcg((const uint32_t*)(qp + 384));
        q[2] = __ldcg((const uint32_t*)(qp + 128)); q[3] = __ldcg((const uint32_t*)(qp + 384 + 128));
        if (t == 0) { q[4] = __ldcg((const uint32_t*)(qp + 256)); q[5] = __ldcg((const uint32_t*)(qp + 384 + 256)); }
        else q[4] = q[5] = !fast ? 0u : (t == 1 ? 0x42fe47c0u   : (t == 2 ? 0x3b80bf16u   : 0u));
        q[6] = __shfl_sync(0xffffffffu, zero, 0); q[7] = __shfl_sync(0xffffffffu, zero, 1);
        float SA[32], SB_[32], O[12];
        uint32_t P[16];
#pragma unroll
        for (int i = 0; i < 12; i++) O[i] = 0.f;
        keep<12>(O); keep<8>(q);
        if (fast) {
            mbar_wait(BAR_FULLKV, ph);
            WG_FENCE();
            qk(SA, q, dk0); WG_COMMIT();
            qk(SB_, q, dk0 + (6144 >> 4)); WG_COMMIT();
#pragma unroll 1
            for (int s = 0; s < 8; s++) {
                const uint64_t so = (uint64_t)(s * (24576 >> 4));
                const uint64_t dk = dk0 + so, dv = dv0 + so;
#pragma unroll
                for (int h = 0; h < 4; h++) {
                    float* S = (h & 1) ? SB_ : SA;
                    WG_WAIT(1);
                    keep<32>(S); keep<12>(O);
                    if (h == 0 && elect && s > 0) mbar_arrive(BAR_EMPTYKV + 8 * (s - 1));
                    if (h & 1) exps<1>(S, P, c3f00); else exps<0>(S, P, c3f00);
                    keep<16>(P);
                    WG_FENCE();
                    pv(O, P, dv + h * (6144 >> 4)); WG_COMMIT();
                    qk(S, q, (h >= 2 && s == 7) ? dk : dk + (h + 2) * (6144 >> 4)); WG_COMMIT();
                    if (h == 1 && s < 7) mbar_wait(BAR_FULLKV + 8 * (s + 1), ph);
                    if (h == 0 && warp == 1) {
                        const int sl = (s + 6) & 7; const bool prev = s < 2;
                        if ((sl & 3) == wg && (prev ? r > 0 : has_next)) kv_refill(sl, prev ? ph ^ 1 : ph, prev ? src_cur : src_next, lane);
                    }
                }
            }
            WG_WAIT(0);
            keep<12>(O); keep<32>(SA); keep<32>(SB_);
        } else {
            float m0 = -INFINITY, m1 = -INFINITY;
#pragma unroll 1
            for (int s = 0; s < 8; s++) {
                if (warp == 1) {
                    const int sl = (s + 6) & 7; const bool prev = s < 2;
                    if ((sl & 3) == wg && (prev ? r > 0 : has_next)) kv_refill(sl, prev ? ph ^ 1 : ph, prev ? src_cur : src_next, lane);
                }
                mbar_wait(BAR_FULLKV + 8 * s, ph);
#pragma unroll 1
                for (int h = 0; h < 4; h++) {
                    const uint64_t so = (uint64_t)((s * 24576 + h * 6144) >> 4);
                    WG_FENCE();
                    qk(SA, q, dk0 + so); WG_COMMIT();
                    WG_WAIT(0);
                    keep<32>(SA); keep<12>(O);
                    float n0 = m0, n1 = m1;
#pragma unroll
                    for (int i = 0; i < 8; i++) { n0 = fmaxf(n0, fmaxf(SA[4 * i], SA[4 * i + 1])); n1 = fmaxf(n1, fmaxf(SA[4 * i + 2], SA[4 * i + 3])); }
                    n0 = fmaxf(n0, __shfl_xor_sync(0xffffffffu, n0, 1)); n0 = fmaxf(n0, __shfl_xor_sync(0xffffffffu, n0, 2));
                    n1 = fmaxf(n1, __shfl_xor_sync(0xffffffffu, n1, 1)); n1 = fmaxf(n1, __shfl_xor_sync(0xffffffffu, n1, 2));
                    const float f0 = ex2(m0 - n0), f1 = ex2(m1 - n1);
                    m0 = n0; m1 = n1;
#pragma unroll
                    for (int i = 0; i < 3; i++) { O[4 * i] *= f0; O[4 * i + 1] *= f0; O[4 * i + 2] *= f1; O[4 * i + 3] *= f1; }
#pragma unroll
                    for (int i = 0; i < 8; i++) {
                        P[2 * i] = pack_bf16(ex2(SA[4 * i] - m0), ex2(SA[4 * i + 1] - m0));
                        P[2 * i + 1] = pack_bf16(ex2(SA[4 * i + 2] - m1), ex2(SA[4 * i + 3] - m1));
                    }
                    keep<16>(P); keep<12>(O);
                    WG_FENCE();
                    pv(O, P, dv0 + so); WG_COMMIT();
                    WG_WAIT(0);
                    keep<12>(O);
                }
                if (elect && s < 7) mbar_arrive(BAR_EMPTYKV + 8 * s);
            }
        }
        if (elect) mbar_arrive(BAR_EMPTYKV + 8 * 7);
        const float l0 = __shfl_sync(0xffffffffu, O[8], (lane & ~3) | 1), l1 = __shfl_sync(0xffffffffu, O[10], (lane & ~3) | 1);
        const float r0 = __frcp_rn(l0), r1 = __frcp_rn(l1);
        uint32_t* op = (uint32_t*)(g_o + (size_t)(rb * 64 + warp * 16 + g) * DM + head * 18) + t;
#pragma unroll
        for (int i = 0; i < 3; i++) {
            if (i < 2 || t == 0) { op[4 * i] = pack_bf16(O[4 * i] * r0, O[4 * i + 1] * r0); op[4 * i + 8 * (DM / 2)] = pack_bf16(O[4 * i + 2] * r1, O[4 * i + 3] * r1); }
        }
        bar_sync(4 + wg, 128);
        if (elect) { __threadfence(); st_release(&g_oflag[rb * 32 + head], epoch + 1); }
    }
}

__global__ void __launch_bounds__(NTHREADS, 1) fused_kernel(const __grid_constant__ Params p) {
    extern __shared__ __align__(1024) uint8_t smem_raw[];
    if ((uint32_t)__cvta_generic_to_shared(smem_raw) != SB) asm volatile("trap;");
    const Sched sc = get_sched();
    if (threadIdx.x == 0) {
        for (int i = 0; i < 9; i++) { mbar_init(BAR_FULLA + 8 * i, 1); mbar_init(BAR_EMPTYA + 8 * i, 2); }
        for (int i = 0; i < 6; i++) { mbar_init(BAR_FULLB + 8 * i, 1); mbar_init(BAR_EMPTYB + 8 * i, 2); }
        for (int i = 0; i < 8; i++) { mbar_init(BAR_FULLKV + 8 * i, 1); mbar_init(BAR_EMPTYKV + 8 * i, 4); }
        mbar_init(BAR_INFO, 1);
        asm volatile("fence.mbarrier_init.release.cluster;" ::: "memory");
    }
    __syncthreads();
    const int wg = __shfl_sync(0xffffffffu, threadIdx.x >> 7, 0);
    const int lane = threadIdx.x & 31;
    const bool elect = (threadIdx.x & 127) == 0;
    TS(wg);

    if (wg == 0) {
        asm volatile("setmaxnreg.dec.sync.aligned.u32 24;");
        const int warp = __shfl_sync(0xffffffffu, threadIdx.x >> 5, 0);
        if (warp == 0) {
            int st = 0; uint32_t ph = 1;
            if (lane == 0) {
                for (int q = 0; q < sc.ntiles; q++) {
                    const int n = q * 8 + sc.j;
                    const bool mini = q == 4;
                    const CUtensorMap* wm = mini ? &p.w1n : (n < 9 ? &p.wqkv : &p.w1);
                    const int chunk = mini ? 69 + sc.j : (n < 9 ? n * 3 : (n - 9) * 3);
                    for (int hs = 0; hs < 18; hs++) {
                        if (q == 0 && !(hs & 1)) { const int kb = hs >> 1; mbar_expect(BAR_FULLA + 8 * kb, 16384); tma2d(A_OFF + kb * 16384, &p.x, kb * 64, sc.m * 128, BAR_FULLA + 8 * kb); }
                        mbar_wait(BAR_EMPTYB + 8 * st, ph);
                        mbar_expect(BAR_FULLB + 8 * st, mini ? 4096 : 12288);
                        tma3d(B_OFF + st * 12288, wm, 0, hs * 32, chunk, BAR_FULLB + 8 * st);
                        if (++st == 6) { st = 0; ph ^= 1; }
                    }
                }
            }
            __syncwarp();
            const unsigned epoch = ld_relaxed(&g_done) / (4 * NCTA);
            if (sc.isG) {
                int sa = 0; uint32_t pa = 0;
                for (int kk = 0; kk < 81; kk++) {
                    if (kk < 72) { if (lane == 0) flag_wait(&g_hflag[sc.m * 72 + kk], epoch + 1); }
                    else {
                        const int c0 = (kk - 72) * 64, h0 = c0 / 18, h1 = (c0 + 63) / 18, hh = h0 + (lane >> 1);
                        if (hh <= h1) flag_wait(&g_oflag[(sc.m * 2 + (lane & 1)) * 32 + hh], epoch + 1);
                    }
                    __syncwarp();
                    if (lane == 0) {
                        fence_async();
                        mbar_wait(BAR_EMPTYA + 8 * sa, pa);
                        mbar_expect(BAR_FULLA + 8 * sa, 16384);
                        if (kk < 72) tma2d(A_OFF + sa * 16384, &p.h, kk * 64, sc.m * 128, BAR_FULLA + 8 * sa);
                        else tma2d(A_OFF + sa * 16384, &p.o, (kk - 72) * 64, sc.m * 128, BAR_FULLA + 8 * sa);
                        for (int half = 0; half < 2; half++) {
                            mbar_wait(BAR_EMPTYB + 8 * st, ph);
                            mbar_expect(BAR_FULLB + 8 * st, 12288);
                            if (kk < 72) { for (int c = 0; c < 3; c++) tma5d(B_OFF + st * 12288 + c * 4096, &p.w2, sc.j * 192 + c * 64, kk * 2 + half, BAR_FULLB + 8 * st); }
                            else tma3d(B_OFF + st * 12288, &p.wo, 0, (kk - 72) * 64 + half * 32, sc.j * 3, BAR_FULLB + 8 * st);
                            if (++st == 6) { st = 0; ph ^= 1; }
                        }
                    }
                    if (++sa == 9) { sa = 0; pa ^= 1; }
                }
            } else {
                if (lane < 9) flag_wait(&g_qkv[lane], (epoch + 1) * 16);
                __syncwarp();
                if (lane == 0) {
                    fence_async();
                    const uint8_t* src = g_kv + (size_t)(sc.aidx >> 3) * 196608;
                    for (int s = 0; s < 8; s++) {
                        if (sc.ntiles > 0) {
                            if (s < 6) { mbar_wait(BAR_EMPTYA + 8 * ((3 * s) >> 1), 0); mbar_wait(BAR_EMPTYA + 8 * ((3 * s + 2) >> 1), 0); }
                            else { mbar_wait(BAR_EMPTYB + 8 * (2 * s - 12), ph); mbar_wait(BAR_EMPTYB + 8 * (2 * s - 11), ph); }
                        }
                        mbar_expect(BAR_FULLKV + 8 * s, 24576);
                        bulk_load(KV_OFF + s * 24576, src + s * 24576, 24576, BAR_FULLKV + 8 * s);
                    }
                }
                __syncwarp();
            }
        } else if (warp == 1 && sc.ntiles > 0) {
            if (lane == 0) {
                const unsigned epoch = ld_relaxed(&g_done) / (4 * NCTA);
                flag_wait(&g_prep, (epoch + 1) * 2 * NCTA);
                fence_async();
                mbar_expect(BAR_INFO, 4 * 1536 + (sc.isG ? 512 : 0) + 1024);
                for (int q = 0; q < 4; q++) bulk_load(INFO_OFF + q * 1536, g_colinfo + (q * 8 + sc.j) * 192, 1536, BAR_INFO);
                if (sc.isG) bulk_load(INFO_OFF + 4 * 1536, g_colinfo + 32 * 192 + sc.j * 64, 512, BAR_INFO);
                bulk_load(ROWS_OFF, g_rowstat + sc.m * 128, 1024, BAR_INFO);
            }
            __syncwarp();
        }
        if (!sc.isG) {
            bar_sync(2, 256);
            asm volatile("setmaxnreg.inc.sync.aligned.u32 128;");
            const unsigned epoch = ld_relaxed(&g_done) / (4 * NCTA);
            TS(8);
            attention(sc.aidx, 0, epoch);
            TS(12);
        }
        bar_sync(4, 128);
        if (elect) red_release(&g_done, 1);
    } else if (wg == 3) {
        if (blockIdx.x < 99) {
            const int tid = threadIdx.x & 127, cg = tid & 7, rg = tid >> 3;
            const int col = blockIdx.x * 64 + cg * 8;
            const __nv_bfloat16* w; int ld;
            if (col < 1728) { w = p.wqkvp + col; ld = 1728; } else { w = p.w1p + (col - 1728); ld = FF; }
            float s[8] = {0.f, 0.f, 0.f, 0.f, 0.f, 0.f, 0.f, 0.f};
#pragma unroll 1
            for (int b = 0; b < 3; b++) {
                uint4 v[12];
#pragma unroll
                for (int i = 0; i < 12; i++) v[i] = __ldg((const uint4*)(w + (size_t)((b * 12 + i) * 16 + rg) * ld));
#pragma unroll
                for (int i = 0; i < 12; i++) {
                    s[0] += bf_lo(v[i].x); s[1] += bf_hi(v[i].x); s[2] += bf_lo(v[i].y); s[3] += bf_hi(v[i].y);
                    s[4] += bf_lo(v[i].z); s[5] += bf_hi(v[i].z); s[6] += bf_lo(v[i].w); s[7] += bf_hi(v[i].w);
                }
            }
#pragma unroll
            for (int e = 0; e < 8; e++) { s[e] += __shfl_xor_sync(0xffffffffu, s[e], 8); s[e] += __shfl_xor_sync(0xffffffffu, s[e], 16); }
            float* scr = (float*)(smem_raw + (INFO_OFF - SB));
            if (lane < 8) {
#pragma unroll
                for (int e = 0; e < 8; e++) scr[(tid >> 5) * 64 + cg * 8 + e] = s[e];
            }
            bar_sync(7, 128);
            if (tid < 64) {
                const int c = blockIdx.x * 64 + tid;
                const float cs = scr[tid] + scr[64 + tid] + scr[128 + tid] + scr[192 + tid];
                g_colinfo[c] = make_float2(cs, c < 1728 ? 0.f : 0.5f * __bfloat162float(p.b1p[c - 1728]));
            }
        }
        bar_sync(7, 128);
        if (elect) { __threadfence(); red_release(&g_prep, 1); }
        asm volatile("setmaxnreg.dec.sync.aligned.u32 24;");
        if (!sc.isG) {
            bar_sync(1, 256);
            asm volatile("setmaxnreg.inc.sync.aligned.u32 128;");
            const unsigned epoch = ld_relaxed(&g_done) / (4 * NCTA);
            TS(11);
            attention(sc.aidx, 3, epoch);
            TS(15);
        }
        bar_sync(7, 128);
        if (elect) red_release(&g_done, 1);
    } else {
        const int warp = __shfl_sync(0xffffffffu, (threadIdx.x >> 5) & 3, 0), g = lane >> 2, t = lane & 3;
        if (wg == 2) {
            if (blockIdx.x < 128) {
                const int row = blockIdx.x * 16 + warp * 4 + (lane >> 3);
                const uint4* xr = (const uint4*)(p.xp + (size_t)row * DM) + (lane & 7);
                uint4 v[9];
#pragma unroll
                for (int i = 0; i < 9; i++) v[i] = __ldg(xr + i * 8);
                float s = 0.f;
#pragma unroll
                for (int i = 0; i < 9; i++) s += ((bf_lo(v[i].x) + bf_hi(v[i].x)) + (bf_lo(v[i].y) + bf_hi(v[i].y))) + ((bf_lo(v[i].z) + bf_hi(v[i].z)) + (bf_lo(v[i].w) + bf_hi(v[i].w)));
                s += __shfl_xor_sync(0xffffffffu, s, 1); s += __shfl_xor_sync(0xffffffffu, s, 2); s += __shfl_xor_sync(0xffffffffu, s, 4);
                const float mean = s * (1.0f / DM);
                float q = 0.f;
#pragma unroll
                for (int i = 0; i < 9; i++) {
                    const uint32_t w4[4] = {v[i].x, v[i].y, v[i].z, v[i].w};
#pragma unroll
                    for (int e = 0; e < 4; e++) { const float a = bf_lo(w4[e]) - mean, b = bf_hi(w4[e]) - mean; q = fmaf(a, a, q); q = fmaf(b, b, q); }
                }
                q += __shfl_xor_sync(0xffffffffu, q, 1); q += __shfl_xor_sync(0xffffffffu, q, 2); q += __shfl_xor_sync(0xffffffffu, q, 4);
                const float hr = 0.5f * rsqrtf(q * (1.0f / DM) + 1e-5f);
                if ((lane & 7) == 0) g_rowstat[row] = make_float2(hr, -hr * mean);
            }
            bar_sync(6, 128);
            if (elect) { __threadfence(); red_release(&g_prep, 1); }
        }
        asm volatile("setmaxnreg.inc.sync.aligned.u32 232;");
        const unsigned epoch = ld_relaxed(&g_done) / (4 * NCTA);
        {
            float acc0[96], acc1[96];
#pragma unroll 1
            for (int q = wg - 1; q < 4 && q < sc.ntiles; q += 2) {
                const int n = q * 8 + sc.j;
                gemm1_mainloop<24>(acc0, acc1, q, q < 2, q == sc.ntiles - 1, q < sc.ntiles - 1, elect);
                TS(16 + q);
                if (q < 2) mbar_wait(BAR_INFO, 0);
                if (n < 9) {
                    epilogue_qkv(acc0, acc1, INFO_OFF + q * 1536, sc.m, n, warp, g, t);
                    bar_sync(4 + wg, 128);
                    if (elect) { __threadfence(); red_release(&g_qkv[n], 1); }
                } else {
                    epilogue_gelu<24>(acc0, acc1, INFO_OFF + q * 1536, sc.m, (n - 9) * 192, warp, g, t);
                    bar_sync(4 + wg, 128);
                    if ((threadIdx.x & 127) < 3) { __threadfence(); st_release(&g_hflag[sc.m * 72 + (n - 9) * 3 + (threadIdx.x & 127)], epoch + 1); }
                }
                TS(21 + q);
            }
        }
        if (sc.isG) {
            if (wg == 1) {
                float acc0[32], acc1[32];
                gemm1_mainloop<8>(acc0, acc1, 4, false, true, true, elect);
                epilogue_gelu<8>(acc0, acc1, INFO_OFF + 4 * 1536, sc.m, 23 * 192 + sc.j * 64, warp, g, t);
                bar_sync(4 + wg, 128);
                if (elect) { __threadfence(); st_release(&g_hflag[sc.m * 72 + 69 + sc.j], epoch + 1); }
            } else bar_sync(9, 256);
            TS(7 + wg);
            float acc[96];
#pragma unroll
            for (int i = 0; i < 96; i++) acc[i] = 0.f;
            keep<96>(acc);
            constexpr uint64_t dB = mkdesc(B_OFF, 4096, 1024, 1);
            const uint64_t dA = mkdesc(A_OFF + (wg - 1) * 8192, 16, 1024, 1);
#pragma unroll 1
            for (int k9 = 0; k9 < 9; k9++) {
                const uint32_t pa = (k9 + 1) & 1, pb = (15 + 3 * k9) & 1;
#pragma unroll
                for (int hs = 0; hs < 18; hs++) {
                    const int kb = hs >> 1, half = hs & 1, st = hs % 6;
                    if (half == 0) mbar_wait(BAR_FULLA + 8 * kb, pa);
                    mbar_wait(BAR_FULLB + 8 * st, pb ^ ((hs / 6) & 1));
                    WG_FENCE();
#pragma unroll
                    for (int k = 0; k < 2; k++) {
                        const uint64_t a = dA + (uint64_t)((kb * 16384 + (half * 2 + k) * 32) >> 4);
                        const uint64_t b = dB + (uint64_t)((st * 12288 + k * 2048) >> 4);
                        mma_n192_ss<1>(acc, a, b);
                    }
                    WG_COMMIT();
                    {
                        WG_WAIT(1);
                        if (elect && (hs > 0 || k9 > 0)) {
                            mbar_arrive(BAR_EMPTYB + 8 * ((hs + 5) % 6));
                            if (half == 0) mbar_arrive(BAR_EMPTYA + 8 * ((kb + 8) % 9));
                        }
                    }
                }
            }
            WG_WAIT(0);
            keep<96>(acc);
            TS(11 + wg);
            const size_t off = (size_t)(sc.m * 128 + (wg - 1) * 64 + warp * 16 + g) * DM + sc.j * 192 + 2 * t;
            const uint32_t* xr = (const uint32_t*)(p.xp + off);
            const uint32_t* br = (const uint32_t*)(p.b2p + sc.j * 192 + 2 * t);
            uint32_t* orow = (uint32_t*)(p.out + off);
#pragma unroll
            for (int i = 0; i < 24; i++) {
                const uint32_t b = __ldg(br + 4 * i), x0 = __ldg(xr + 4 * i), x1 = __ldg(xr + 4 * i + 8 * (DM / 2));
                orow[4 * i] = pack_bf16(acc[4 * i] + bf_lo(b) + bf_lo(x0), acc[4 * i + 1] + bf_hi(b) + bf_hi(x0));
                orow[4 * i + 8 * (DM / 2)] = pack_bf16(acc[4 * i + 2] + bf_lo(b) + bf_lo(x1), acc[4 * i + 3] + bf_hi(b) + bf_hi(x1));
            }
            TS(13 + wg);
        } else {
            asm volatile("setmaxnreg.dec.sync.aligned.u32 128;");
            bar_arrive(wg, 256);
            TS(8 + wg);
            attention(sc.aidx, wg, epoch);
            TS(12 + wg);
        }
        bar_sync(4 + wg, 128);
        if (elect) red_release(&g_done, 1);
    }
}

typedef CUresult (*EncFn)(CUtensorMap*, CUtensorMapDataType, cuuint32_t, void*, const cuuint64_t*, const cuuint64_t*, const cuuint32_t*,
                          const cuuint32_t*, CUtensorMapInterleave, CUtensorMapSwizzle, CUtensorMapL2promotion, CUtensorMapFloatOOBfill);

void make_map(EncFn enc, CUtensorMap* m, const void* ptr, int rank, const cuuint64_t* dims, const cuuint64_t* strides, const cuuint32_t* box) {
    cuuint32_t es[5] = {1, 1, 1, 1, 1};
    enc(m, CU_TENSOR_MAP_DATA_TYPE_BFLOAT16, rank, const_cast<void*>(ptr), dims, strides, box, es, CU_TENSOR_MAP_INTERLEAVE_NONE,
        CU_TENSOR_MAP_SWIZZLE_128B, CU_TENSOR_MAP_L2_PROMOTION_L2_256B, CU_TENSOR_MAP_FLOAT_OOB_FILL_NONE);
}
void make_act_map(EncFn enc, CUtensorMap* m, const void* ptr, int cols) {
    cuuint64_t d[2] = {(cuuint64_t)cols, SEQ}, s[1] = {(cuuint64_t)cols * 2}; cuuint32_t b[2] = {64, 128};
    make_map(enc, m, ptr, 2, d, s, b);
}
void make_w_map(EncFn enc, CUtensorMap* m, const void* ptr, int rows, int cols, int nchunk) {
    cuuint64_t d[3] = {64, (cuuint64_t)rows, (cuuint64_t)cols / 64}, s[2] = {(cuuint64_t)cols * 2, 128}; cuuint32_t b[3] = {64, 32, (cuuint32_t)nchunk};
    make_map(enc, m, ptr, 3, d, s, b);
}

}

extern "C" void kernel_launch(void* const* d_in, const int* in_sizes, int n_in, void* d_out, int out_size) {
    static Params prm;
    static bool ready = false;
    static const void* key[9];
    bool same = ready && key[8] == d_out;
    for (int i = 0; i < 8 && same; i++) same = key[i] == d_in[i];
    if (!same) {
        EncFn enc = nullptr; cudaDriverEntryPointQueryResult qr;
        cudaGetDriverEntryPoint("cuTensorMapEncodeTiled", (void**)&enc, cudaEnableDefault, &qr);
        void *hp, *op;
        cudaGetSymbolAddress(&hp, g_h); cudaGetSymbolAddress(&op, g_o);
        make_act_map(enc, &prm.x, d_in[0], DM);
        make_act_map(enc, &prm.h, hp, FF);
        make_act_map(enc, &prm.o, op, DM);
        make_w_map(enc, &prm.wqkv, d_in[1], DM, 1728, 3);
        make_w_map(enc, &prm.w1, d_in[4], DM, FF, 3);
        make_w_map(enc, &prm.w1n, d_in[4], DM, FF, 1);
        make_w_map(enc, &prm.wo, d_in[2], DM, DM, 3);
        {
            cuuint64_t d[5] = {DM, 2, 4, 4, FF / 32}, s[4] = {DM * 2, 8 * DM * 2, 2 * DM * 2, 32 * DM * 2}; cuuint32_t b[5] = {64, 2, 4, 4, 1};
            make_map(enc, &prm.w2, d_in[6], 5, d, s, b);
        }
        prm.xp = (const __nv_bfloat16*)d_in[0]; prm.wqkvp = (const __nv_bfloat16*)d_in[1]; prm.w1p = (const __nv_bfloat16*)d_in[4];
        prm.b1p = (const __nv_bfloat16*)d_in[5]; prm.b2p = (const __nv_bfloat16*)d_in[7]; prm.out = (__nv_bfloat16*)d_out;
        cudaFuncSetAttribute(fused_kernel, cudaFuncAttributeMaxDynamicSharedMemorySize, SMEM_BYTES);
        for (int i = 0; i < 8; i++) key[i] = d_in[i];
        key[8] = d_out; ready = true;
    }
    fused_kernel<<<NCTA, NTHREADS, SMEM_BYTES, cudaStreamPerThread>>>(prm);
}
```

```cpp
#include <cuda_runtime.h>
#include <cuda_bf16.h>
#include <cuda.h>
#include <stdint.h>

#define QSTR 432
#define L2PROMO CU_TENSOR_MAP_L2_PROMOTION_L2_128B
namespace {

constexpr int SEQ = 2048, DM = 576, FF = 4608, NH = 32;
constexpr int NCTA = 132, NTHREADS = 512, NACTA = 84;
#define KVLAG 5
constexpr uint32_t POLYMASK = 0xAD6Bu;

constexpr uint32_t SB = 0x400;
constexpr uint32_t A_OFF = SB;
constexpr uint32_t B_OFF = SB + 9 * 16384;
constexpr uint32_t Q_OFF = SB, Q2_OFF = SB + 12288 + 8 * 24576;
constexpr uint32_t KV_OFF = SB + 12288;
constexpr uint32_t BAR_OFF = B_OFF + 6 * 12288;
constexpr uint32_t BAR_FULLA = BAR_OFF, BAR_EMPTYA = BAR_FULLA + 72, BAR_FULLB = BAR_EMPTYA + 72, BAR_EMPTYB = BAR_FULLB + 48,
                   BAR_FULLKV = BAR_EMPTYB + 48, BAR_EMPTYKV = BAR_FULLKV + 64, BAR_FULLW = BAR_EMPTYKV + 64, BAR_EMPTYW = BAR_FULLW + 72,
                   BAR_INFO = BAR_EMPTYW + 72, BAR_DEP = BAR_INFO + 16, BAR_WDONE = BAR_DEP + 13 * 8, FAST_OFF = BAR_WDONE + 8, BMAX_OFF = FAST_OFF + 4;
constexpr int NBARS = 9 + 9 + 6 + 6 + 8 + 8 + 9 + 9 + 2 + 13 + 1;
static_assert(NBARS % 16 == 0, "barrier init");
constexpr uint32_t ONE_OFF = BAR_OFF + 768;
constexpr uint32_t B2_OFF = ONE_OFF + 896;
constexpr uint32_t BIAS_OFF = BAR_OFF + 3072;
constexpr uint32_t SMEM_END = BIAS_OFF + 3072;
static_assert(B2_OFF + 768 <= BIAS_OFF && BIAS_OFF % 1024 == 0, "smem map");
constexpr uint32_t SMEM_BYTES = SMEM_END - SB;
static_assert(SMEM_BYTES <= 232448, "smem");

__device__ __align__(1024) __nv_bfloat16 g_h[SEQ * FF];
__device__ __align__(1024) uint8_t g_o[SEQ * DM * 2];
__device__ __align__(1024) uint8_t g_qkv[96 * 98304];
__device__ unsigned long long g_bound[24 * 16];
__device__ unsigned g_done;
__device__ unsigned g_qkvcnt;
__device__ unsigned g_hflag[16 * 32];
#define XS 4
__device__ __align__(16) float4 g_part[4 * XS * 4 * 512];
__device__ unsigned g_pflag[4 * 4 * 8];
__device__ unsigned g_oflag[32 * 32];
#define TS(i)
#define TS2(i)

struct Params {
    const __nv_bfloat16* xp; const __nv_bfloat16* wqkvp; const __nv_bfloat16* w1p; const __nv_bfloat16* b1p; const __nv_bfloat16* b2p;
    const __nv_bfloat16* w2p; const __nv_bfloat16* wop;
    __nv_bfloat16* out;
    CUtensorMap x, wq4, wq5, w1n, w1, h, w2, wo, wol, outm;
};

template<int N> __device__ __forceinline__ void mma_ssp(float* d, uint64_t da, uint64_t db, int sd);
template<> __device__ __forceinline__ void mma_ssp<8>(float* d, uint64_t da, uint64_t db, int sd) {
    asm volatile("{\n.reg .pred p;\nsetp.ne.b32 p, %6, 0;\nwgmma.mma_async.sync.aligned.m64n8k16.f32.bf16.bf16 {%0,%1,%2,%3}, %4, %5, p, 1, 1, 0, 1;\n}\n"
      : "+f"(d[0]),"+f"(d[1]),"+f"(d[2]),"+f"(d[3])
      : "l"(da), "l"(db), "r"(sd));
}
template<> __device__ __forceinline__ void mma_ssp<16>(float* d, uint64_t da, uint64_t db, int sd) {
    asm volatile("{\n.reg .pred p;\nsetp.ne.b32 p, %10, 0;\nwgmma.mma_async.sync.aligned.m64n16k16.f32.bf16.bf16 {%0,%1,%2,%3,%4,%5,%6,%7}, %8, %9, p, 1, 1, 0, 1;\n}\n"
      : "+f"(d[0]),"+f"(d[1]),"+f"(d[2]),"+f"(d[3]),"+f"(d[4]),"+f"(d[5]),"+f"(d[6]),"+f"(d[7])
      : "l"(da), "l"(db), "r"(sd));
}
template<> __device__ __forceinline__ void mma_ssp<24>(float* d, uint64_t da, uint64_t db, int sd) {
    asm volatile("{\n.reg .pred p;\nsetp.ne.b32 p, %14, 0;\nwgmma.mma_async.sync.aligned.m64n24k16.f32.bf16.bf16 {%0,%1,%2,%3,%4,%5,%6,%7,%8,%9,%10,%11}, %12, %13, p, 1, 1, 0, 1;\n}\n"
      : "+f"(d[0]),"+f"(d[1]),"+f"(d[2]),"+f"(d[3]),"+f"(d[4]),"+f"(d[5]),"+f"(d[6]),"+f"(d[7]),"+f"(d[8]),"+f"(d[9]),"+f"(d[10]),"+f"(d[11])
      : "l"(da), "l"(db), "r"(sd));
}
template<> __device__ __forceinline__ void mma_ssp<32>(float* d, uint64_t da, uint64_t db, int sd) {
    asm volatile("{\n.reg .pred p;\nsetp.ne.b32 p, %18, 0;\nwgmma.mma_async.sync.aligned.m64n32k16.f32.bf16.bf16 {%0,%1,%2,%3,%4,%5,%6,%7,%8,%9,%10,%11,%12,%13,%14,%15}, %16, %17, p, 1, 1, 0, 1;\n}\n"
      : "+f"(d[0]),"+f"(d[1]),"+f"(d[2]),"+f"(d[3]),"+f"(d[4]),"+f"(d[5]),"+f"(d[6]),"+f"(d[7]),"+f"(d[8]),"+f"(d[9]),"+f"(d[10]),"+f"(d[11]),"+f"(d[12]),"+f"(d[13]),"+f"(d[14]),"+f"(d[15])
      : "l"(da), "l"(db), "r"(sd));
}
template<> __device__ __forceinline__ void mma_ssp<40>(float* d, uint64_t da, uint64_t db, int sd) {
    asm volatile("{\n.reg .pred p;\nsetp.ne.b32 p, %22, 0;\nwgmma.mma_async.sync.aligned.m64n40k16.f32.bf16.bf16 {%0,%1,%2,%3,%4,%5,%6,%7,%8,%9,%10,%11,%12,%13,%14,%15,%16,%17,%18,%19}, %20, %21, p, 1, 1, 0, 1;\n}\n"
      : "+f"(d[0]),"+f"(d[1]),"+f"(d[2]),"+f"(d[3]),"+f"(d[4]),"+f"(d[5]),"+f"(d[6]),"+f"(d[7]),"+f"(d[8]),"+f"(d[9]),"+f"(d[10]),"+f"(d[11]),"+f"(d[12]),"+f"(d[13]),"+f"(d[14]),"+f"(d[15]),"+f"(d[16]),"+f"(d[17]),"+f"(d[18]),"+f"(d[19])
      : "l"(da), "l"(db), "r"(sd));
}
template<> __device__ __forceinline__ void mma_ssp<48>(float* d, uint64_t da, uint64_t db, int sd) {
    asm volatile("{\n.reg .pred p;\nsetp.ne.b32 p, %26, 0;\nwgmma.mma_async.sync.aligned.m64n48k16.f32.bf16.bf16 {%0,%1,%2,%3,%4,%5,%6,%7,%8,%9,%10,%11,%12,%13,%14,%15,%16,%17,%18,%19,%20,%21,%22,%23}, %24, %25, p, 1, 1, 0, 1;\n}\n"
      : "+f"(d[0]),"+f"(d[1]),"+f"(d[2]),"+f"(d[3]),"+f"(d[4]),"+f"(d[5]),"+f"(d[6]),"+f"(d[7]),"+f"(d[8]),"+f"(d[9]),"+f"(d[10]),"+f"(d[11]),"+f"(d[12]),"+f"(d[13]),"+f"(d[14]),"+f"(d[15]),"+f"(d[16]),"+f"(d[17]),"+f"(d[18]),"+f"(d[19]),"+f"(d[20]),"+f"(d[21]),"+f"(d[22]),"+f"(d[23])
      : "l"(da), "l"(db), "r"(sd));
}
template<> __device__ __forceinline__ void mma_ssp<56>(float* d, uint64_t da, uint64_t db, int sd) {
    asm volatile("{\n.reg .pred p;\nsetp.ne.b32 p, %30, 0;\nwgmma.mma_async.sync.aligned.m64n56k16.f32.bf16.bf16 {%0,%1,%2,%3,%4,%5,%6,%7,%8,%9,%10,%11,%12,%13,%14,%15,%16,%17,%18,%19,%20,%21,%22,%23,%24,%25,%26,%27}, %28, %29, p, 1, 1, 0, 1;\n}\n"
      : "+f"(d[0]),"+f"(d[1]),"+f"(d[2]),"+f"(d[3]),"+f"(d[4]),"+f"(d[5]),"+f"(d[6]),"+f"(d[7]),"+f"(d[8]),"+f"(d[9]),"+f"(d[10]),"+f"(d[11]),"+f"(d[12]),"+f"(d[13]),"+f"(d[14]),"+f"(d[15]),"+f"(d[16]),"+f"(d[17]),"+f"(d[18]),"+f"(d[19]),"+f"(d[20]),"+f"(d[21]),"+f"(d[22]),"+f"(d[23]),"+f"(d[24]),"+f"(d[25]),"+f"(d[26]),"+f"(d[27])
      : "l"(da), "l"(db), "r"(sd));
}
template<> __device__ __forceinline__ void mma_ssp<64>(float* d, uint64_t da, uint64_t db, int sd) {
    asm volatile("{\n.reg .pred p;\nsetp.ne.b32 p, %34, 0;\nwgmma.mma_async.sync.aligned.m64n64k16.f32.bf16.bf16 {%0,%1,%2,%3,%4,%5,%6,%7,%8,%9,%10,%11,%12,%13,%14,%15,%16,%17,%18,%19,%20,%21,%22,%23,%24,%25,%26,%27,%28,%29,%30,%31}, %32, %33, p, 1, 1, 0, 1;\n}\n"
      : "+f"(d[0]),"+f"(d[1]),"+f"(d[2]),"+f"(d[3]),"+f"(d[4]),"+f"(d[5]),"+f"(d[6]),"+f"(d[7]),"+f"(d[8]),"+f"(d[9]),"+f"(d[10]),"+f"(d[11]),"+f"(d[12]),"+f"(d[13]),"+f"(d[14]),"+f"(d[15]),"+f"(d[16]),"+f"(d[17]),"+f"(d[18]),"+f"(d[19]),"+f"(d[20]),"+f"(d[21]),"+f"(d[22]),"+f"(d[23]),"+f"(d[24]),"+f"(d[25]),"+f"(d[26]),"+f"(d[27]),"+f"(d[28]),"+f"(d[29]),"+f"(d[30]),"+f"(d[31])
      : "l"(da), "l"(db), "r"(sd));
}
template<> __device__ __forceinline__ void mma_ssp<80>(float* d, uint64_t da, uint64_t db, int sd) {
    asm volatile("{\n.reg .pred p;\nsetp.ne.b32 p, %42, 0;\nwgmma.mma_async.sync.aligned.m64n80k16.f32.bf16.bf16 {%0,%1,%2,%3,%4,%5,%6,%7,%8,%9,%10,%11,%12,%13,%14,%15,%16,%17,%18,%19,%20,%21,%22,%23,%24,%25,%26,%27,%28,%29,%30,%31,%32,%33,%34,%35,%36,%37,%38,%39}, %40, %41, p, 1, 1, 0, 1;\n}\n"
      : "+f"(d[0]),"+f"(d[1]),"+f"(d[2]),"+f"(d[3]),"+f"(d[4]),"+f"(d[5]),"+f"(d[6]),"+f"(d[7]),"+f"(d[8]),"+f"(d[9]),"+f"(d[10]),"+f"(d[11]),"+f"(d[12]),"+f"(d[13]),"+f"(d[14]),"+f"(d[15]),"+f"(d[16]),"+f"(d[17]),"+f"(d[18]),"+f"(d[19]),"+f"(d[20]),"+f"(d[21]),"+f"(d[22]),"+f"(d[23]),"+f"(d[24]),"+f"(d[25]),"+f"(d[26]),"+f"(d[27]),"+f"(d[28]),"+f"(d[29]),"+f"(d[30]),"+f"(d[31]),"+f"(d[32]),"+f"(d[33]),"+f"(d[34]),"+f"(d[35]),"+f"(d[36]),"+f"(d[37]),"+f"(d[38]),"+f"(d[39])
      : "l"(da), "l"(db), "r"(sd));
}
template<> __device__ __forceinline__ void mma_ssp<128>(float* d, uint64_t da, uint64_t db, int sd) {
    asm volatile("{\n.reg .pred p;\nsetp.ne.b32 p, %66, 0;\nwgmma.mma_async.sync.aligned.m64n128k16.f32.bf16.bf16 {%0,%1,%2,%3,%4,%5,%6,%7,%8,%9,%10,%11,%12,%13,%14,%15,%16,%17,%18,%19,%20,%21,%22,%23,%24,%25,%26,%27,%28,%29,%30,%31,%32,%33,%34,%35,%36,%37,%38,%39,%40,%41,%42,%43,%44,%45,%46,%47,%48,%49,%50,%51,%52,%53,%54,%55,%56,%57,%58,%59,%60,%61,%62,%63}, %64, %65, p, 1, 1, 0, 1;\n}\n"
      : "+f"(d[0]),"+f"(d[1]),"+f"(d[2]),"+f"(d[3]),"+f"(d[4]),"+f"(d[5]),"+f"(d[6]),"+f"(d[7]),"+f"(d[8]),"+f"(d[9]),"+f"(d[10]),"+f"(d[11]),"+f"(d[12]),"+f"(d[13]),"+f"(d[14]),"+f"(d[15]),"+f"(d[16]),"+f"(d[17]),"+f"(d[18]),"+f"(d[19]),"+f"(d[20]),"+f"(d[21]),"+f"(d[22]),"+f"(d[23]),"+f"(d[24]),"+f"(d[25]),"+f"(d[26]),"+f"(d[27]),"+f"(d[28]),"+f"(d[29]),"+f"(d[30]),"+f"(d[31]),"+f"(d[32]),"+f"(d[33]),"+f"(d[34]),"+f"(d[35]),"+f"(d[36]),"+f"(d[37]),"+f"(d[38]),"+f"(d[39]),"+f"(d[40]),"+f"(d[41]),"+f"(d[42]),"+f"(d[43]),"+f"(d[44]),"+f"(d[45]),"+f"(d[46]),"+f"(d[47]),"+f"(d[48]),"+f"(d[49]),"+f"(d[50]),"+f"(d[51]),"+f"(d[52]),"+f"(d[53]),"+f"(d[54]),"+f"(d[55]),"+f"(d[56]),"+f"(d[57]),"+f"(d[58]),"+f"(d[59]),"+f"(d[60]),"+f"(d[61]),"+f"(d[62]),"+f"(d[63])
      : "l"(da), "l"(db), "r"(sd));
}
template<> __device__ __forceinline__ void mma_ssp<152>(float* d, uint64_t da, uint64_t db, int sd) {
    asm volatile("{\n.reg .pred p;\nsetp.ne.b32 p, %78, 0;\nwgmma.mma_async.sync.aligned.m64n152k16.f32.bf16.bf16 {%0,%1,%2,%3,%4,%5,%6,%7,%8,%9,%10,%11,%12,%13,%14,%15,%16,%17,%18,%19,%20,%21,%22,%23,%24,%25,%26,%27,%28,%29,%30,%31,%32,%33,%34,%35,%36,%37,%38,%39,%40,%41,%42,%43,%44,%45,%46,%47,%48,%49,%50,%51,%52,%53,%54,%55,%56,%57,%58,%59,%60,%61,%62,%63,%64,%65,%66,%67,%68,%69,%70,%71,%72,%73,%74,%75}, %76, %77, p, 1, 1, 0, 1;\n}\n"
      : "+f"(d[0]),"+f"(d[1]),"+f"(d[2]),"+f"(d[3]),"+f"(d[4]),"+f"(d[5]),"+f"(d[6]),"+f"(d[7]),"+f"(d[8]),"+f"(d[9]),"+f"(d[10]),"+f"(d[11]),"+f"(d[12]),"+f"(d[13]),"+f"(d[14]),"+f"(d[15]),"+f"(d[16]),"+f"(d[17]),"+f"(d[18]),"+f"(d[19]),"+f"(d[20]),"+f"(d[21]),"+f"(d[22]),"+f"(d[23]),"+f"(d[24]),"+f"(d[25]),"+f"(d[26]),"+f"(d[27]),"+f"(d[28]),"+f"(d[29]),"+f"(d[30]),"+f"(d[31]),"+f"(d[32]),"+f"(d[33]),"+f"(d[34]),"+f"(d[35]),"+f"(d[36]),"+f"(d[37]),"+f"(d[38]),"+f"(d[39]),"+f"(d[40]),"+f"(d[41]),"+f"(d[42]),"+f"(d[43]),"+f"(d[44]),"+f"(d[45]),"+f"(d[46]),"+f"(d[47]),"+f"(d[48]),"+f"(d[49]),"+f"(d[50]),"+f"(d[51]),"+f"(d[52]),"+f"(d[53]),"+f"(d[54]),"+f"(d[55]),"+f"(d[56]),"+f"(d[57]),"+f"(d[58]),"+f"(d[59]),"+f"(d[60]),"+f"(d[61]),"+f"(d[62]),"+f"(d[63]),"+f"(d[64]),"+f"(d[65]),"+f"(d[66]),"+f"(d[67]),"+f"(d[68]),"+f"(d[69]),"+f"(d[70]),"+f"(d[71]),"+f"(d[72]),"+f"(d[73]),"+f"(d[74]),"+f"(d[75])
      : "l"(da), "l"(db), "r"(sd));
}
template<> __device__ __forceinline__ void mma_ssp<160>(float* d, uint64_t da, uint64_t db, int sd) {
    asm volatile("{\n.reg .pred p;\nsetp.ne.b32 p, %82, 0;\nwgmma.mma_async.sync.aligned.m64n160k16.f32.bf16.bf16 {%0,%1,%2,%3,%4,%5,%6,%7,%8,%9,%10,%11,%12,%13,%14,%15,%16,%17,%18,%19,%20,%21,%22,%23,%24,%25,%26,%27,%28,%29,%30,%31,%32,%33,%34,%35,%36,%37,%38,%39,%40,%41,%42,%43,%44,%45,%46,%47,%48,%49,%50,%51,%52,%53,%54,%55,%56,%57,%58,%59,%60,%61,%62,%63,%64,%65,%66,%67,%68,%69,%70,%71,%72,%73,%74,%75,%76,%77,%78,%79}, %80, %81, p, 1, 1, 0, 1;\n}\n"
      : "+f"(d[0]),"+f"(d[1]),"+f"(d[2]),"+f"(d[3]),"+f"(d[4]),"+f"(d[5]),"+f"(d[6]),"+f"(d[7]),"+f"(d[8]),"+f"(d[9]),"+f"(d[10]),"+f"(d[11]),"+f"(d[12]),"+f"(d[13]),"+f"(d[14]),"+f"(d[15]),"+f"(d[16]),"+f"(d[17]),"+f"(d[18]),"+f"(d[19]),"+f"(d[20]),"+f"(d[21]),"+f"(d[22]),"+f"(d[23]),"+f"(d[24]),"+f"(d[25]),"+f"(d[26]),"+f"(d[27]),"+f"(d[28]),"+f"(d[29]),"+f"(d[30]),"+f"(d[31]),"+f"(d[32]),"+f"(d[33]),"+f"(d[34]),"+f"(d[35]),"+f"(d[36]),"+f"(d[37]),"+f"(d[38]),"+f"(d[39]),"+f"(d[40]),"+f"(d[41]),"+f"(d[42]),"+f"(d[43]),"+f"(d[44]),"+f"(d[45]),"+f"(d[46]),"+f"(d[47]),"+f"(d[48]),"+f"(d[49]),"+f"(d[50]),"+f"(d[51]),"+f"(d[52]),"+f"(d[53]),"+f"(d[54]),"+f"(d[55]),"+f"(d[56]),"+f"(d[57]),"+f"(d[58]),"+f"(d[59]),"+f"(d[60]),"+f"(d[61]),"+f"(d[62]),"+f"(d[63]),"+f"(d[64]),"+f"(d[65]),"+f"(d[66]),"+f"(d[67]),"+f"(d[68]),"+f"(d[69]),"+f"(d[70]),"+f"(d[71]),"+f"(d[72]),"+f"(d[73]),"+f"(d[74]),"+f"(d[75]),"+f"(d[76]),"+f"(d[77]),"+f"(d[78]),"+f"(d[79])
      : "l"(da), "l"(db), "r"(sd));
}
template<> __device__ __forceinline__ void mma_ssp<168>(float* d, uint64_t da, uint64_t db, int sd) {
    asm volatile("{\n.reg .pred p;\nsetp.ne.b32 p, %86, 0;\nwgmma.mma_async.sync.aligned.m64n168k16.f32.bf16.bf16 {%0,%1,%2,%3,%4,%5,%6,%7,%8,%9,%10,%11,%12,%13,%14,%15,%16,%17,%18,%19,%20,%21,%22,%23,%24,%25,%26,%27,%28,%29,%30,%31,%32,%33,%34,%35,%36,%37,%38,%39,%40,%41,%42,%43,%44,%45,%46,%47,%48,%49,%50,%51,%52,%53,%54,%55,%56,%57,%58,%59,%60,%61,%62,%63,%64,%65,%66,%67,%68,%69,%70,%71,%72,%73,%74,%75,%76,%77,%78,%79,%80,%81,%82,%83}, %84, %85, p, 1, 1, 0, 1;\n}\n"
      : "+f"(d[0]),"+f"(d[1]),"+f"(d[2]),"+f"(d[3]),"+f"(d[4]),"+f"(d[5]),"+f"(d[6]),"+f"(d[7]),"+f"(d[8]),"+f"(d[9]),"+f"(d[10]),"+f"(d[11]),"+f"(d[12]),"+f"(d[13]),"+f"(d[14]),"+f"(d[15]),"+f"(d[16]),"+f"(d[17]),"+f"(d[18]),"+f"(d[19]),"+f"(d[20]),"+f"(d[21]),"+f"(d[22]),"+f"(d[23]),"+f"(d[24]),"+f"(d[25]),"+f"(d[26]),"+f"(d[27]),"+f"(d[28]),"+f"(d[29]),"+f"(d[30]),"+f"(d[31]),"+f"(d[32]),"+f"(d[33]),"+f"(d[34]),"+f"(d[35]),"+f"(d[36]),"+f"(d[37]),"+f"(d[38]),"+f"(d[39]),"+f"(d[40]),"+f"(d[41]),"+f"(d[42]),"+f"(d[43]),"+f"(d[44]),"+f"(d[45]),"+f"(d[46]),"+f"(d[47]),"+f"(d[48]),"+f"(d[49]),"+f"(d[50]),"+f"(d[51]),"+f"(d[52]),"+f"(d[53]),"+f"(d[54]),"+f"(d[55]),"+f"(d[56]),"+f"(d[57]),"+f"(d[58]),"+f"(d[59]),"+f"(d[60]),"+f"(d[61]),"+f"(d[62]),"+f"(d[63]),"+f"(d[64]),"+f"(d[65]),"+f"(d[66]),"+f"(d[67]),"+f"(d[68]),"+f"(d[69]),"+f"(d[70]),"+f"(d[71]),"+f"(d[72]),"+f"(d[73]),"+f"(d[74]),"+f"(d[75]),"+f"(d[76]),"+f"(d[77]),"+f"(d[78]),"+f"(d[79]),"+f"(d[80]),"+f"(d[81]),"+f"(d[82]),"+f"(d[83])
      : "l"(da), "l"(db), "r"(sd));
}
template<> __device__ __forceinline__ void mma_ssp<176>(float* d, uint64_t da, uint64_t db, int sd) {
    asm volatile("{\n.reg .pred p;\nsetp.ne.b32 p, %90, 0;\nwgmma.mma_async.sync.aligned.m64n176k16.f32.bf16.bf16 {%0,%1,%2,%3,%4,%5,%6,%7,%8,%9,%10,%11,%12,%13,%14,%15,%16,%17,%18,%19,%20,%21,%22,%23,%24,%25,%26,%27,%28,%29,%30,%31,%32,%33,%34,%35,%36,%37,%38,%39,%40,%41,%42,%43,%44,%45,%46,%47,%48,%49,%50,%51,%52,%53,%54,%55,%56,%57,%58,%59,%60,%61,%62,%63,%64,%65,%66,%67,%68,%69,%70,%71,%72,%73,%74,%75,%76,%77,%78,%79,%80,%81,%82,%83,%84,%85,%86,%87}, %88, %89, p, 1, 1, 0, 1;\n}\n"
      : "+f"(d[0]),"+f"(d[1]),"+f"(d[2]),"+f"(d[3]),"+f"(d[4]),"+f"(d[5]),"+f"(d[6]),"+f"(d[7]),"+f"(d[8]),"+f"(d[9]),"+f"(d[10]),"+f"(d[11]),"+f"(d[12]),"+f"(d[13]),"+f"(d[14]),"+f"(d[15]),"+f"(d[16]),"+f"(d[17]),"+f"(d[18]),"+f"(d[19]),"+f"(d[20]),"+f"(d[21]),"+f"(d[22]),"+f"(d[23]),"+f"(d[24]),"+f"(d[25]),"+f"(d[26]),"+f"(d[27]),"+f"(d[28]),"+f"(d[29]),"+f"(d[30]),"+f"(d[31]),"+f"(d[32]),"+f"(d[33]),"+f"(d[34]),"+f"(d[35]),"+f"(d[36]),"+f"(d[37]),"+f"(d[38]),"+f"(d[39]),"+f"(d[40]),"+f"(d[41]),"+f"(d[42]),"+f"(d[43]),"+f"(d[44]),"+f"(d[45]),"+f"(d[46]),"+f"(d[47]),"+f"(d[48]),"+f"(d[49]),"+f"(d[50]),"+f"(d[51]),"+f"(d[52]),"+f"(d[53]),"+f"(d[54]),"+f"(d[55]),"+f"(d[56]),"+f"(d[57]),"+f"(d[58]),"+f"(d[59]),"+f"(d[60]),"+f"(d[61]),"+f"(d[62]),"+f"(d[63]),"+f"(d[64]),"+f"(d[65]),"+f"(d[66]),"+f"(d[67]),"+f"(d[68]),"+f"(d[69]),"+f"(d[70]),"+f"(d[71]),"+f"(d[72]),"+f"(d[73]),"+f"(d[74]),"+f"(d[75]),"+f"(d[76]),"+f"(d[77]),"+f"(d[78]),"+f"(d[79]),"+f"(d[80]),"+f"(d[81]),"+f"(d[82]),"+f"(d[83]),"+f"(d[84]),"+f"(d[85]),"+f"(d[86]),"+f"(d[87])
      : "l"(da), "l"(db), "r"(sd));
}
template<> __device__ __forceinline__ void mma_ssp<184>(float* d, uint64_t da, uint64_t db, int sd) {
    asm volatile("{\n.reg .pred p;\nsetp.ne.b32 p, %94, 0;\nwgmma.mma_async.sync.aligned.m64n184k16.f32.bf16.bf16 {%0,%1,%2,%3,%4,%5,%6,%7,%8,%9,%10,%11,%12,%13,%14,%15,%16,%17,%18,%19,%20,%21,%22,%23,%24,%25,%26,%27,%28,%29,%30,%31,%32,%33,%34,%35,%36,%37,%38,%39,%40,%41,%42,%43,%44,%45,%46,%47,%48,%49,%50,%51,%52,%53,%54,%55,%56,%57,%58,%59,%60,%61,%62,%63,%64,%65,%66,%67,%68,%69,%70,%71,%72,%73,%74,%75,%76,%77,%78,%79,%80,%81,%82,%83,%84,%85,%86,%87,%88,%89,%90,%91}, %92, %93, p, 1, 1, 0, 1;\n}\n"
      : "+f"(d[0]),"+f"(d[1]),"+f"(d[2]),"+f"(d[3]),"+f"(d[4]),"+f"(d[5]),"+f"(d[6]),"+f"(d[7]),"+f"(d[8]),"+f"(d[9]),"+f"(d[10]),"+f"(d[11]),"+f"(d[12]),"+f"(d[13]),"+f"(d[14]),"+f"(d[15]),"+f"(d[16]),"+f"(d[17]),"+f"(d[18]),"+f"(d[19]),"+f"(d[20]),"+f"(d[21]),"+f"(d[22]),"+f"(d[23]),"+f"(d[24]),"+f"(d[25]),"+f"(d[26]),"+f"(d[27]),"+f"(d[28]),"+f"(d[29]),"+f"(d[30]),"+f"(d[31]),"+f"(d[32]),"+f"(d[33]),"+f"(d[34]),"+f"(d[35]),"+f"(d[36]),"+f"(d[37]),"+f"(d[38]),"+f"(d[39]),"+f"(d[40]),"+f"(d[41]),"+f"(d[42]),"+f"(d[43]),"+f"(d[44]),"+f"(d[45]),"+f"(d[46]),"+f"(d[47]),"+f"(d[48]),"+f"(d[49]),"+f"(d[50]),"+f"(d[51]),"+f"(d[52]),"+f"(d[53]),"+f"(d[54]),"+f"(d[55]),"+f"(d[56]),"+f"(d[57]),"+f"(d[58]),"+f"(d[59]),"+f"(d[60]),"+f"(d[61]),"+f"(d[62]),"+f"(d[63]),"+f"(d[64]),"+f"(d[65]),"+f"(d[66]),"+f"(d[67]),"+f"(d[68]),"+f"(d[69]),"+f"(d[70]),"+f"(d[71]),"+f"(d[72]),"+f"(d[73]),"+f"(d[74]),"+f"(d[75]),"+f"(d[76]),"+f"(d[77]),"+f"(d[78]),"+f"(d[79]),"+f"(d[80]),"+f"(d[81]),"+f"(d[82]),"+f"(d[83]),"+f"(d[84]),"+f"(d[85]),"+f"(d[86]),"+f"(d[87]),"+f"(d[88]),"+f"(d[89]),"+f"(d[90]),"+f"(d[91])
      : "l"(da), "l"(db), "r"(sd));
}
template<> __device__ __forceinline__ void mma_ssp<192>(float* d, uint64_t da, uint64_t db, int sd) {
    asm volatile("{\n.reg .pred p;\nsetp.ne.b32 p, %98, 0;\nwgmma.mma_async.sync.aligned.m64n192k16.f32.bf16.bf16 {%0,%1,%2,%3,%4,%5,%6,%7,%8,%9,%10,%11,%12,%13,%14,%15,%16,%17,%18,%19,%20,%21,%22,%23,%24,%25,%26,%27,%28,%29,%30,%31,%32,%33,%34,%35,%36,%37,%38,%39,%40,%41,%42,%43,%44,%45,%46,%47,%48,%49,%50,%51,%52,%53,%54,%55,%56,%57,%58,%59,%60,%61,%62,%63,%64,%65,%66,%67,%68,%69,%70,%71,%72,%73,%74,%75,%76,%77,%78,%79,%80,%81,%82,%83,%84,%85,%86,%87,%88,%89,%90,%91,%92,%93,%94,%95}, %96, %97, p, 1, 1, 0, 1;\n}\n"
      : "+f"(d[0]),"+f"(d[1]),"+f"(d[2]),"+f"(d[3]),"+f"(d[4]),"+f"(d[5]),"+f"(d[6]),"+f"(d[7]),"+f"(d[8]),"+f"(d[9]),"+f"(d[10]),"+f"(d[11]),"+f"(d[12]),"+f"(d[13]),"+f"(d[14]),"+f"(d[15]),"+f"(d[16]),"+f"(d[17]),"+f"(d[18]),"+f"(d[19]),"+f"(d[20]),"+f"(d[21]),"+f"(d[22]),"+f"(d[23]),"+f"(d[24]),"+f"(d[25]),"+f"(d[26]),"+f"(d[27]),"+f"(d[28]),"+f"(d[29]),"+f"(d[30]),"+f"(d[31]),"+f"(d[32]),"+f"(d[33]),"+f"(d[34]),"+f"(d[35]),"+f"(d[36]),"+f"(d[37]),"+f"(d[38]),"+f"(d[39]),"+f"(d[40]),"+f"(d[41]),"+f"(d[42]),"+f"(d[43]),"+f"(d[44]),"+f"(d[45]),"+f"(d[46]),"+f"(d[47]),"+f"(d[48]),"+f"(d[49]),"+f"(d[50]),"+f"(d[51]),"+f"(d[52]),"+f"(d[53]),"+f"(d[54]),"+f"(d[55]),"+f"(d[56]),"+f"(d[57]),"+f"(d[58]),"+f"(d[59]),"+f"(d[60]),"+f"(d[61]),"+f"(d[62]),"+f"(d[63]),"+f"(d[64]),"+f"(d[65]),"+f"(d[66]),"+f"(d[67]),"+f"(d[68]),"+f"(d[69]),"+f"(d[70]),"+f"(d[71]),"+f"(d[72]),"+f"(d[73]),"+f"(d[74]),"+f"(d[75]),"+f"(d[76]),"+f"(d[77]),"+f"(d[78]),"+f"(d[79]),"+f"(d[80]),"+f"(d[81]),"+f"(d[82]),"+f"(d[83]),"+f"(d[84]),"+f"(d[85]),"+f"(d[86]),"+f"(d[87]),"+f"(d[88]),"+f"(d[89]),"+f"(d[90]),"+f"(d[91]),"+f"(d[92]),"+f"(d[93]),"+f"(d[94]),"+f"(d[95])
      : "l"(da), "l"(db), "r"(sd));
}
template<> __device__ __forceinline__ void mma_ssp<200>(float* d, uint64_t da, uint64_t db, int sd) {
    asm volatile("{\n.reg .pred p;\nsetp.ne.b32 p, %102, 0;\nwgmma.mma_async.sync.aligned.m64n200k16.f32.bf16.bf16 {%0,%1,%2,%3,%4,%5,%6,%7,%8,%9,%10,%11,%12,%13,%14,%15,%16,%17,%18,%19,%20,%21,%22,%23,%24,%25,%26,%27,%28,%29,%30,%31,%32,%33,%34,%35,%36,%37,%38,%39,%40,%41,%42,%43,%44,%45,%46,%47,%48,%49,%50,%51,%52,%53,%54,%55,%56,%57,%58,%59,%60,%61,%62,%63,%64,%65,%66,%67,%68,%69,%70,%71,%72,%73,%74,%75,%76,%77,%78,%79,%80,%81,%82,%83,%84,%85,%86,%87,%88,%89,%90,%91,%92,%93,%94,%95,%96,%97,%98,%99}, %100, %101, p, 1, 1, 0, 1;\n}\n"
      : "+f"(d[0]),"+f"(d[1]),"+f"(d[2]),"+f"(d[3]),"+f"(d[4]),"+f"(d[5]),"+f"(d[6]),"+f"(d[7]),"+f"(d[8]),"+f"(d[9]),"+f"(d[10]),"+f"(d[11]),"+f"(d[12]),"+f"(d[13]),"+f"(d[14]),"+f"(d[15]),"+f"(d[16]),"+f"(d[17]),"+f"(d[18]),"+f"(d[19]),"+f"(d[20]),"+f"(d[21]),"+f"(d[22]),"+f"(d[23]),"+f"(d[24]),"+f"(d[25]),"+f"(d[26]),"+f"(d[27]),"+f"(d[28]),"+f"(d[29]),"+f"(d[30]),"+f"(d[31]),"+f"(d[32]),"+f"(d[33]),"+f"(d[34]),"+f"(d[35]),"+f"(d[36]),"+f"(d[37]),"+f"(d[38]),"+f"(d[39]),"+f"(d[40]),"+f"(d[41]),"+f"(d[42]),"+f"(d[43]),"+f"(d[44]),"+f"(d[45]),"+f"(d[46]),"+f"(d[47]),"+f"(d[48]),"+f"(d[49]),"+f"(d[50]),"+f"(d[51]),"+f"(d[52]),"+f"(d[53]),"+f"(d[54]),"+f"(d[55]),"+f"(d[56]),"+f"(d[57]),"+f"(d[58]),"+f"(d[59]),"+f"(d[60]),"+f"(d[61]),"+f"(d[62]),"+f"(d[63]),"+f"(d[64]),"+f"(d[65]),"+f"(d[66]),"+f"(d[67]),"+f"(d[68]),"+f"(d[69]),"+f"(d[70]),"+f"(d[71]),"+f"(d[72]),"+f"(d[73]),"+f"(d[74]),"+f"(d[75]),"+f"(d[76]),"+f"(d[77]),"+f"(d[78]),"+f"(d[79]),"+f"(d[80]),"+f"(d[81]),"+f"(d[82]),"+f"(d[83]),"+f"(d[84]),"+f"(d[85]),"+f"(d[86]),"+f"(d[87]),"+f"(d[88]),"+f"(d[89]),"+f"(d[90]),"+f"(d[91]),"+f"(d[92]),"+f"(d[93]),"+f"(d[94]),"+f"(d[95]),"+f"(d[96]),"+f"(d[97]),"+f"(d[98]),"+f"(d[99])
      : "l"(da), "l"(db), "r"(sd));
}
template<int SD> __device__ __forceinline__ void mma_n192_ss(float* d, uint64_t da, uint64_t db) {
    asm volatile("wgmma.mma_async.sync.aligned.m64n192k16.f32.bf16.bf16 {%0,%1,%2,%3,%4,%5,%6,%7,%8,%9,%10,%11,%12,%13,%14,%15,%16,%17,%18,%19,%20,%21,%22,%23,%24,%25,%26,%27,%28,%29,%30,%31,%32,%33,%34,%35,%36,%37,%38,%39,%40,%41,%42,%43,%44,%45,%46,%47,%48,%49,%50,%51,%52,%53,%54,%55,%56,%57,%58,%59,%60,%61,%62,%63,%64,%65,%66,%67,%68,%69,%70,%71,%72,%73,%74,%75,%76,%77,%78,%79,%80,%81,%82,%83,%84,%85,%86,%87,%88,%89,%90,%91,%92,%93,%94,%95}, %96, %97, %98, 1, 1, 0, 1;\n"
      : "+f"(d[0]),"+f"(d[1]),"+f"(d[2]),"+f"(d[3]),"+f"(d[4]),"+f"(d[5]),"+f"(d[6]),"+f"(d[7]),"+f"(d[8]),"+f"(d[9]),"+f"(d[10]),"+f"(d[11]),"+f"(d[12]),"+f"(d[13]),"+f"(d[14]),"+f"(d[15]),"+f"(d[16]),"+f"(d[17]),"+f"(d[18]),"+f"(d[19]),"+f"(d[20]),"+f"(d[21]),"+f"(d[22]),"+f"(d[23]),"+f"(d[24]),"+f"(d[25]),"+f"(d[26]),"+f"(d[27]),"+f"(d[28]),"+f"(d[29]),"+f"(d[30]),"+f"(d[31]),"+f"(d[32]),"+f"(d[33]),"+f"(d[34]),"+f"(d[35]),"+f"(d[36]),"+f"(d[37]),"+f"(d[38]),"+f"(d[39]),"+f"(d[40]),"+f"(d[41]),"+f"(d[42]),"+f"(d[43]),"+f"(d[44]),"+f"(d[45]),"+f"(d[46]),"+f"(d[47]),"+f"(d[48]),"+f"(d[49]),"+f"(d[50]),"+f"(d[51]),"+f"(d[52]),"+f"(d[53]),"+f"(d[54]),"+f"(d[55]),"+f"(d[56]),"+f"(d[57]),"+f"(d[58]),"+f"(d[59]),"+f"(d[60]),"+f"(d[61]),"+f"(d[62]),"+f"(d[63]),"+f"(d[64]),"+f"(d[65]),"+f"(d[66]),"+f"(d[67]),"+f"(d[68]),"+f"(d[69]),"+f"(d[70]),"+f"(d[71]),"+f"(d[72]),"+f"(d[73]),"+f"(d[74]),"+f"(d[75]),"+f"(d[76]),"+f"(d[77]),"+f"(d[78]),"+f"(d[79]),"+f"(d[80]),"+f"(d[81]),"+f"(d[82]),"+f"(d[83]),"+f"(d[84]),"+f"(d[85]),"+f"(d[86]),"+f"(d[87]),"+f"(d[88]),"+f"(d[89]),"+f"(d[90]),"+f"(d[91]),"+f"(d[92]),"+f"(d[93]),"+f"(d[94]),"+f"(d[95])
      : "l"(da), "l"(db), "n"(SD));
}
template<int SD> __device__ __forceinline__ void mma_n64_ss(float* d, uint64_t da, uint64_t db) {
    asm volatile("wgmma.mma_async.sync.aligned.m64n64k16.f32.bf16.bf16 {%0,%1,%2,%3,%4,%5,%6,%7,%8,%9,%10,%11,%12,%13,%14,%15,%16,%17,%18,%19,%20,%21,%22,%23,%24,%25,%26,%27,%28,%29,%30,%31}, %32, %33, %34, 1, 1, 0, 1;\n"
      : "+f"(d[0]),"+f"(d[1]),"+f"(d[2]),"+f"(d[3]),"+f"(d[4]),"+f"(d[5]),"+f"(d[6]),"+f"(d[7]),"+f"(d[8]),"+f"(d[9]),"+f"(d[10]),"+f"(d[11]),"+f"(d[12]),"+f"(d[13]),"+f"(d[14]),"+f"(d[15]),"+f"(d[16]),"+f"(d[17]),"+f"(d[18]),"+f"(d[19]),"+f"(d[20]),"+f"(d[21]),"+f"(d[22]),"+f"(d[23]),"+f"(d[24]),"+f"(d[25]),"+f"(d[26]),"+f"(d[27]),"+f"(d[28]),"+f"(d[29]),"+f"(d[30]),"+f"(d[31])
      : "l"(da), "l"(db), "n"(SD));
}
template<int SD> __device__ __forceinline__ void mma_n64_rs(float* d, uint32_t a0, uint32_t a1, uint32_t a2, uint32_t a3, uint64_t db) {
    asm volatile("wgmma.mma_async.sync.aligned.m64n64k16.f32.bf16.bf16 {%0,%1,%2,%3,%4,%5,%6,%7,%8,%9,%10,%11,%12,%13,%14,%15,%16,%17,%18,%19,%20,%21,%22,%23,%24,%25,%26,%27,%28,%29,%30,%31}, {%32,%33,%34,%35}, %36, %37, 1, 1, 0;\n"
      : "+f"(d[0]),"+f"(d[1]),"+f"(d[2]),"+f"(d[3]),"+f"(d[4]),"+f"(d[5]),"+f"(d[6]),"+f"(d[7]),"+f"(d[8]),"+f"(d[9]),"+f"(d[10]),"+f"(d[11]),"+f"(d[12]),"+f"(d[13]),"+f"(d[14]),"+f"(d[15]),"+f"(d[16]),"+f"(d[17]),"+f"(d[18]),"+f"(d[19]),"+f"(d[20]),"+f"(d[21]),"+f"(d[22]),"+f"(d[23]),"+f"(d[24]),"+f"(d[25]),"+f"(d[26]),"+f"(d[27]),"+f"(d[28]),"+f"(d[29]),"+f"(d[30]),"+f"(d[31])
      : "r"(a0), "r"(a1), "r"(a2), "r"(a3), "l"(db), "n"(SD));
}
template<int SD> __device__ __forceinline__ void mma_n24_rs(float* d, uint32_t a0, uint32_t a1, uint32_t a2, uint32_t a3, uint64_t db) {
    asm volatile("wgmma.mma_async.sync.aligned.m64n24k16.f32.bf16.bf16 {%0,%1,%2,%3,%4,%5,%6,%7,%8,%9,%10,%11}, {%12,%13,%14,%15}, %16, %17, 1, 1, 1;\n"
      : "+f"(d[0]),"+f"(d[1]),"+f"(d[2]),"+f"(d[3]),"+f"(d[4]),"+f"(d[5]),"+f"(d[6]),"+f"(d[7]),"+f"(d[8]),"+f"(d[9]),"+f"(d[10]),"+f"(d[11])
      : "r"(a0), "r"(a1), "r"(a2), "r"(a3), "l"(db), "n"(SD));
}

__host__ __device__ constexpr uint64_t mkdesc(uint32_t addr, uint32_t lbo, uint32_t sbo, uint32_t swz) {
    return (uint64_t)((addr & 0x3FFFF) >> 4) | ((uint64_t)(lbo >> 4) << 16) | ((uint64_t)(sbo >> 4) << 32) | ((uint64_t)swz << 62);
}
#define WG_FENCE() asm volatile("wgmma.fence.sync.aligned;" ::: "memory")
#define WG_COMMIT() asm volatile("wgmma.commit_group.sync.aligned;" ::: "memory")
#define WG_WAIT(n) asm volatile("wgmma.wait_group.sync.aligned " #n ";" ::: "memory")
template<int N> __device__ __forceinline__ void keep(float* r) {
#pragma unroll
    for (int i = 0; i < N; i++) asm volatile("" : "+f"(r[i]) :: "memory");
}
template<int N> __device__ __forceinline__ void kill(float* r) {
#pragma unroll
    for (int i = 0; i < N; i++) asm volatile("" : "=f"(r[i]));
}
template<int N> __device__ __forceinline__ void keep(uint32_t* r) {
#pragma unroll
    for (int i = 0; i < N; i++) asm volatile("" : "+r"(r[i]) :: "memory");
}
__device__ __forceinline__ uint32_t cl(uint32_t a) { return a + ((blockIdx.x & 1) << 24); }
__device__ __forceinline__ void mbar_init(uint32_t a, uint32_t c) { asm volatile("mbarrier.init.shared::cta.b64 [%0], %1;" :: "r"(cl(a)), "r"(c) : "memory"); }
__device__ __forceinline__ void mbar_expect(uint32_t a, uint32_t b) { asm volatile("mbarrier.arrive.expect_tx.shared::cta.b64 _, [%0], %1;" :: "r"(cl(a)), "r"(b) : "memory"); }
__device__ __forceinline__ void mbar_arrive(uint32_t a) { asm volatile("mbarrier.arrive.shared::cta.b64 _, [%0];" :: "r"(cl(a)) : "memory"); }
__device__ __forceinline__ void mbar_arrive_n(uint32_t a, uint32_t n) { asm volatile("mbarrier.arrive.shared::cta.b64 _, [%0], %1;" :: "r"(cl(a)), "r"(n) : "memory"); }
__device__ __forceinline__ void mbar_wait(uint32_t a, uint32_t ph) {
    asm volatile("{\n.reg .pred p, q;\n.reg .u32 n;\nmov.u32 n, 0;\n"
        "LW:\nmbarrier.try_wait.parity.shared::cta.b64 p, [%0], %1;\n@p bra LD;\n"
        "add.u32 n, n, 1;\nsetp.gt.u32 q, n, 2000000;\n@q trap;\nbra LW;\nLD:\n}" :: "r"(cl(a)), "r"(ph) : "memory");
}
__device__ __forceinline__ void flag_wait(const unsigned* p, unsigned target) {
    asm volatile("{\n.reg .pred p, q;\n.reg .u32 n, v;\nmov.u32 n, 0;\n"
        "LW:\nld.acquire.gpu.global.u32 v, [%0];\nsub.u32 v, v, %1;\nsetp.ge.s32 p, v, 0;\n@p bra LD;\n"
        "nanosleep.u32 100;\nadd.u32 n, n, 1;\nsetp.gt.u32 q, n, 4000000;\n@q trap;\nbra LW;\nLD:\n}" :: "l"(p), "r"(target) : "memory");
}
__device__ __forceinline__ void red_release(unsigned* p, unsigned v) { asm volatile("red.release.gpu.global.add.u32 [%0], %1;" :: "l"(p), "r"(v) : "memory"); }
__device__ __forceinline__ void red_relaxed(unsigned* p, unsigned v) { asm volatile("red.relaxed.gpu.global.add.u32 [%0], %1;" :: "l"(p), "r"(v) : "memory"); }
__device__ __forceinline__ void st_release(unsigned* p, unsigned v) { asm volatile("st.release.gpu.global.u32 [%0], %1;" :: "l"(p), "r"(v) : "memory"); }
__device__ __forceinline__ unsigned ld_relaxed(const unsigned* p) { unsigned v; asm volatile("ld.relaxed.gpu.global.u32 %0, [%1];" : "=r"(v) : "l"(p) : "memory"); return v; }
__device__ __forceinline__ unsigned ld_acquire(const unsigned* p) { unsigned v; asm volatile("ld.acquire.gpu.global.u32 %0, [%1];" : "=r"(v) : "l"(p) : "memory"); return v; }
__device__ __forceinline__ unsigned get_tag() { return ld_relaxed(&g_done) / (4 * NCTA) + 1; }
__device__ __forceinline__ unsigned long long ld_tagged(const unsigned long long* p) {
    unsigned long long v; asm volatile("ld.relaxed.gpu.global.b64 %0, [%1];" : "=l"(v) : "l"(p) : "memory"); return v;
}
__device__ __forceinline__ void fence_async() { asm volatile("fence.proxy.async;" ::: "memory"); }
__device__ __forceinline__ void bar_sync(int id, int n) { asm volatile("bar.sync %0, %1;" :: "r"(id), "r"(n) : "memory"); }
__device__ __forceinline__ void bar_arrive(int id, int n) { asm volatile("bar.arrive %0, %1;" :: "r"(id), "r"(n) : "memory"); }
#define ELECT_BEGIN "{\n.reg .pred p, e;\nelect.sync _|p, 0xffffffff;\nsetp.ne.and.u32 e, %1, 0, p;\n@e mbarrier.arrive.expect_tx.shared::cta.b64 _, [%0], %1;\n"
__device__ __forceinline__ void bulk_load(uint32_t dst, const void* src, uint32_t bytes, uint32_t bar, uint32_t tx) {
    asm volatile(ELECT_BEGIN "@p cp.async.bulk.shared::cluster.global.mbarrier::complete_tx::bytes [%2], [%3], %4, [%0];\n}"
        :: "r"(cl(bar)), "r"(tx), "r"(cl(dst)), "l"(src), "r"(bytes) : "memory");
}
__device__ __forceinline__ void send_half(int kb) {
    const uint32_t off = A_OFF + (blockIdx.x & 1) * 8192 + kb * 16384, peer = ((blockIdx.x & 1) ^ 1) << 24;
    asm volatile(ELECT_BEGIN "@p cp.async.bulk.shared::cluster.shared::cta.mbarrier::complete_tx::bytes [%2], [%3], 8192, [%4];\n}"
        :: "r"(cl(BAR_FULLA + 8 * kb)), "r"(8192), "r"(off + peer), "r"(cl(off)), "r"(BAR_FULLA + 8 * kb + peer) : "memory");
}
__device__ __forceinline__ void tma2d(uint32_t dst, const CUtensorMap* m, int c0, int c1, uint32_t bar, uint32_t tx) {
    asm volatile(ELECT_BEGIN "@p cp.async.bulk.tensor.2d.shared::cluster.global.mbarrier::complete_tx::bytes [%2], [%3, {%4, %5}], [%0];\n}"
        :: "r"(cl(bar)), "r"(tx), "r"(cl(dst)), "l"(m), "r"(c0), "r"(c1) : "memory");
}
__device__ __forceinline__ void tma3d(uint32_t dst, const CUtensorMap* m, int c1, int c2, uint32_t bar, uint32_t tx) {
    asm volatile(ELECT_BEGIN "@p cp.async.bulk.tensor.3d.shared::cluster.global.mbarrier::complete_tx::bytes [%2], [%3, {%6, %4, %5}], [%0];\n}"
        :: "r"(cl(bar)), "r"(tx), "r"(cl(dst)), "l"(m), "r"(c1), "r"(c2), "r"(0) : "memory");
}
__device__ __forceinline__ void tma4d(uint32_t dst, const CUtensorMap* m, int c1, int c2, int c3, uint32_t bar, uint32_t tx) {
    asm volatile(ELECT_BEGIN "@p cp.async.bulk.tensor.4d.shared::cluster.global.mbarrier::complete_tx::bytes [%2], [%3, {%7, %4, %5, %6}], [%0];\n}"
        :: "r"(cl(bar)), "r"(tx), "r"(cl(dst)), "l"(m), "r"(c1), "r"(c2), "r"(c3), "r"(0) : "memory");
}
__device__ __forceinline__ void tma5d(uint32_t dst, const CUtensorMap* m, int c3, int c4, uint32_t bar, uint32_t tx) {
    asm volatile(ELECT_BEGIN "@p cp.async.bulk.tensor.5d.shared::cluster.global.mbarrier::complete_tx::bytes [%2], [%3, {%6, %6, %6, %4, %5}], [%0];\n}"
        :: "r"(cl(bar)), "r"(tx), "r"(cl(dst)), "l"(m), "r"(c3), "r"(c4), "r"(0) : "memory");
}
__device__ __forceinline__ uint32_t pack_bf16(float lo, float hi) {
    uint32_t r; asm("cvt.rn.bf16x2.f32 %0, %1, %2;" : "=r"(r) : "f"(hi), "f"(lo)); return r;
}
__device__ __forceinline__ float bf_lo(uint32_t v) { return __uint_as_float(v << 16); }
__device__ __forceinline__ float bf_hi(uint32_t v) { return __uint_as_float(v & 0xffff0000u); }
__device__ __forceinline__ float4 lds128(uint32_t a) { float4 v; asm volatile("ld.shared.v4.f32 {%0,%1,%2,%3}, [%4];" : "=f"(v.x), "=f"(v.y), "=f"(v.z), "=f"(v.w) : "r"(cl(a))); return v; }
__device__ __forceinline__ float2 lds64(uint32_t a) { float2 v; asm volatile("ld.shared.v2.f32 {%0,%1}, [%2];" : "=f"(v.x), "=f"(v.y) : "r"(cl(a))); return v; }
__device__ __forceinline__ uint32_t lds32(uint32_t a) { uint32_t v; asm volatile("ld.shared.u32 %0, [%1];" : "=r"(v) : "r"(cl(a)) : "memory"); return v; }
__device__ __forceinline__ void l2_prefetch(const void* p, uint32_t bytes, uint32_t pause) {
#pragma unroll 1
    for (uint32_t o = (threadIdx.x & 31) * 128; o < bytes; o += 4096) {
        asm volatile("prefetch.global.L2 [%0];" :: "l"((const uint8_t*)p + o) : "memory");
        if (pause) asm volatile("nanosleep.u32 %0;" :: "r"(pause));
    }
    __syncwarp();
}
__device__ __forceinline__ void l2_prefetch_bulk(const void* p, uint32_t bytes) {
    asm volatile("{\n.reg .pred p;\nelect.sync _|p, 0xffffffff;\n@p cp.async.bulk.prefetch.L2.global [%0], %1;\n}" :: "l"(p), "r"(bytes) : "memory");
}
__device__ __forceinline__ float ex2(float x) { float y; asm("ex2.approx.ftz.f32 %0, %1;" : "=f"(y) : "f"(x)); return y; }

__device__ __forceinline__ int cta_m() { return blockIdx.x >> 3; }
__device__ __forceinline__ int cta_j() { return blockIdx.x & 7; }
__device__ __forceinline__ bool cta_isG() { return blockIdx.x < 128 && (blockIdx.x & 7) < 3; }
__device__ __forceinline__ int cta_aidx() { return blockIdx.x >= 128 ? blockIdx.x - 128 : 1 + (blockIdx.x >> 3) * 5 + (blockIdx.x & 7); }

__device__ __forceinline__ int has_mini() { return cta_j() == 0 || cta_j() >= 3; }
__device__ __forceinline__ int num_jobs() { return has_mini() + (cta_isG() ? 4 : 2); }
__device__ __forceinline__ int job_id(int q) {
    const int w = q - has_mini(), j = cta_j();
    return w < 0 ? (j == 0 ? 0 : j - 2) : 6 + (w < 2 ? 8 * w + j : 10 + 3 * w + j);
}
__device__ __forceinline__ int job_chunk(int id) { return id < 6 ? id : 3 * id - 12; }
__device__ __forceinline__ int job_bar(int q) { return q < 3 ? 11 + q : (q == 3 ? 15 : 3); }

template<int J>
__device__ __forceinline__ void qkv_mainloop(uint32_t* v, int wg, bool elect) {
    constexpr int O = (216 * J) % 64, N1 = 64 - O, N2 = 152 + O, NCH = (O + 216 + 63) / 64, NST = NCH == 4 ? 9 : 7;
    constexpr uint64_t dB = mkdesc(B_OFF, 2048, 1024, 1);
    const uint64_t dA = mkdesc(A_OFF, 16, 1024, 1) + (uint64_t)((wg - 1) * (8192 >> 4));
    int st = 0; uint32_t ph = 0;
    float acc[108];
#pragma unroll 1
    for (int ks = 0; ks < 36; ks += 2) {
        int st1 = st + 1; uint32_t ph1 = ph; if (st1 == NST) { st1 = 0; ph1 ^= 1; }
        if ((ks & 3) == 0) mbar_wait(BAR_FULLA + 2 * ks, 0);
        mbar_wait(BAR_FULLW + 8 * st, ph);
        mbar_wait(BAR_FULLW + 8 * st1, ph1);
        const uint64_t a = dA + (uint64_t)((ks >> 2) * (16384 >> 4) + (ks & 3) * 2);
        WG_FENCE();
#pragma unroll
        for (int k = 0; k < 2; k++) {
            const uint64_t b = dB + (uint64_t)((k ? st1 : st) * (NCH * 2048 >> 4));
            if (N2 <= 200) mma_ssp<(N2 <= 200 ? N2 : 128)>(acc + N1 / 2, a + 2 * k, b + (2048 >> 4), ks + k);
            else { mma_ssp<128>(acc + N1 / 2, a + 2 * k, b + (2048 >> 4), ks + k); mma_ssp<80>(acc + N1 / 2 + 64, a + 2 * k, b + (6144 >> 4), ks + k); }
            mma_ssp<N1>(acc, a + 2 * k, b + (2 * O >> 4), ks + k);
        }
        WG_COMMIT();
        WG_WAIT(1);
        if ((threadIdx.x & 127) < 2 && ks > 0) {
            int sp = st - 1 - (threadIdx.x & 1); if (sp < 0) sp += NST;
            mbar_arrive(BAR_EMPTYW + 8 * sp);
        }
        st = st1 + 1; ph = ph1; if (st == NST) { st = 0; ph ^= 1; }
    }
    WG_WAIT(0);
    keep<108>(acc);
    if (elect) mbar_arrive(BAR_WDONE);
    if (wg == 1) TS(16);
    constexpr float QS = 0.23570226f * 1.44269504f;
#pragma unroll
    for (int i = 0; i < 54; i++) v[i] = 216 * J + 8 * (i >> 1) < DM ? pack_bf16(acc[2 * i] * QS, acc[2 * i + 1] * QS) : pack_bf16(acc[2 * i], acc[2 * i + 1]);
}

__device__ __forceinline__ uint64_t sel_desc(int q) { return mkdesc(ONE_OFF, 0, 0, 0) + (uint64_t)(q * (128 >> 4)) + ((uint64_t)((5 - q) * (128 >> 4)) << 16); }
constexpr uint64_t SEL2 = (uint64_t)(128 >> 4) << 16;
constexpr uint64_t BIAS_DESC = mkdesc(BIAS_OFF, 1024, 0, 1);
__device__ __forceinline__ void mini_mainloop(float* acc0, float* acc1, bool elect) {
    constexpr uint64_t dA = mkdesc(A_OFF, 16, 1024, 1), dB = mkdesc(B_OFF, 0, 1024, 1);
    WG_FENCE();
    mma_n64_ss<0>(acc0, sel_desc(0), BIAS_DESC); mma_n64_ss<0>(acc1, sel_desc(0) + SEL2, BIAS_DESC);
    WG_COMMIT();
#pragma unroll 1
    for (int s = 0; s < 6; s++) {
        mbar_wait(BAR_FULLB + 8 * s, 0);
        if (s == 5) bar_arrive(9, 256);
        WG_FENCE();
#pragma unroll
        for (int k = 0; k < 6; k++) {
            const int ks = 6 * s + k;
            const uint64_t a = dA + (uint64_t)((ks >> 2) * (16384 >> 4) + (ks & 3) * 2), b = dB + (uint64_t)(ks * (2048 >> 4));
            mma_n64_ss<1>(acc0, a, b); mma_n64_ss<1>(acc1, a + (8192 >> 4), b);
        }
        WG_COMMIT();
        WG_WAIT(1);
        if (elect && s > 0) mbar_arrive(BAR_EMPTYB + 8 * (s - 1));
    }
    WG_WAIT(0);
    if (elect) mbar_arrive(BAR_EMPTYB + 8 * 5);
    keep<32>(acc0); keep<32>(acc1);
}
__device__ __forceinline__ void job_mainloop(float* acc0, float* acc1, int q, bool g2, uint32_t xa, int t, int wg, bool elect) {
    constexpr uint64_t dB = mkdesc(B_OFF, 4096, 1024, 1);
    const bool last = q == num_jobs() - 1, releaseA = g2 || last, handoff = !g2 && (!last || cta_isG());
    WG_FENCE();
    mma_n192_ss<0>(acc0, sel_desc(g2 ? 5 : q), BIAS_DESC); mma_n192_ss<0>(acc1, sel_desc(g2 ? 5 : q) + SEL2, BIAS_DESC);
    WG_COMMIT();
    if (q > 0) bar_sync(8 + (q & 1), 256);
    const int nturn = g2 ? 27 : 3;
    int grp = 0; uint32_t pa = 1;
#pragma unroll 1
    for (int u = 0; u < nturn; u++) {
        const uint32_t par = (q + u) & 1;
        const bool img = u >= 24;
        if (g2 && (u == 3 || u == 12 || u == 24)) TS2(u == 3 ? 4 : (u == 12 ? 5 : 6));
        if (u == 24) {
            WG_WAIT(0);
            keep<96>(acc0); keep<96>(acc1);
            if (elect) { mbar_arrive(BAR_EMPTYB + 8 * 5); mbar_arrive(BAR_EMPTYA + 8 * 8); }
#pragma unroll
            for (int i2 = 0; i2 < 12; i2++) {
                if ((i2 & 3) == 0) mbar_wait(BAR_FULLA + 8 * (i2 >> 2), pa);
                const float2 b0 = lds64(B2_OFF + 64 * i2 + 8 * t), b1 = lds64(B2_OFF + 64 * i2 + 32 + 8 * t);
#pragma unroll
                for (int mh = 0; mh < 2; mh++) {
                    float* a = (mh ? acc1 : acc0) + 8 * i2;
                    uint32_t r0, r1, r2, r3;
                    asm volatile("ldmatrix.sync.aligned.m8n8.x4.shared.b16 {%0,%1,%2,%3}, [%4];" : "=r"(r0), "=r"(r1), "=r"(r2), "=r"(r3)
                        : "r"(cl((xa ^ ((i2 & 3) << 5)) + (i2 >> 2) * 16384 + mh * 8192)) : "memory");
                    a[0] = fmaf(a[0], 0.5f, bf_lo(r0) + b0.x); a[1] = fmaf(a[1], 0.5f, bf_hi(r0) + b0.y);
                    a[2] = fmaf(a[2], 0.5f, bf_lo(r1) + b0.x); a[3] = fmaf(a[3], 0.5f, bf_hi(r1) + b0.y);
                    a[4] = fmaf(a[4], 0.5f, bf_lo(r2) + b1.x); a[5] = fmaf(a[5], 0.5f, bf_hi(r2) + b1.y);
                    a[6] = fmaf(a[6], 0.5f, bf_lo(r3) + b1.x); a[7] = fmaf(a[7], 0.5f, bf_hi(r3) + b1.y);
                }
            }
            keep<96>(acc0); keep<96>(acc1);
            bar_sync(4 + wg, 128);
            if ((threadIdx.x & 127) < 3) mbar_arrive(BAR_EMPTYA + 8 * (threadIdx.x & 127));
            grp = 1;
        }
        const uint64_t dAu = (img ? mkdesc(A_OFF, 128, 1024, 0) : mkdesc(A_OFF, 16, 1024, 1)) + (uint64_t)(grp * (3 * 16384 >> 4));
        const uint32_t kst = img ? (256 >> 4) : (32 >> 4);
#pragma unroll
        for (int st = 0; st < 6; st++) {
            const int kb = st >> 1, half = st & 1;
            if (half == 0 && g2) mbar_wait(BAR_FULLA + 8 * (3 * grp + kb), pa);
            mbar_wait(BAR_FULLB + 8 * st, par);
            if (st == 5 && u == 2 && handoff) bar_arrive(8 + ((q + 1) & 1), 256);
            WG_FENCE();
#pragma unroll
            for (int k = 0; k < 2; k++) {
                const uint64_t a = dAu + (uint64_t)(kb * (16384 >> 4) + (half * 2 + k) * kst);
                const uint64_t b = dB + (uint64_t)((st * 12288 + k * 2048) >> 4);
                mma_n192_ss<1>(acc0, a, b); mma_n192_ss<1>(acc1, a + (8192 >> 4), b);
            }
            WG_COMMIT();
            WG_WAIT(1);
            if (elect && (st > 0 || (u > 0 && u != 24))) {
                mbar_arrive(BAR_EMPTYB + 8 * ((st + 5) % 6));
                if (half == 0 && releaseA) mbar_arrive(BAR_EMPTYA + 8 * (kb == 0 && grp == 0 ? 8 : 3 * grp + kb - 1));
            }
        }
        if (++grp == 3) { grp = 0; pa ^= 1; }
    }
    WG_WAIT(0);
    if (elect && !g2) { mbar_arrive(BAR_EMPTYB + 8 * 5); if (releaseA) mbar_arrive(BAR_EMPTYA + 8 * 8); }
    keep<96>(acc0); keep<96>(acc1);
}

__device__ __forceinline__ void epilogue_gelu(const float* acc, __nv_bfloat16* hp, bool narrow, uint32_t pace) {
#pragma unroll
    for (int i4 = 0; i4 < 6; i4++) {
        if (i4 == 2 && narrow) break;
        float z[16];
#define XX(e) acc[4 * (8 * (i4 >> 1) + (i4 & 1) + 2 * ((e) >> 2)) + ((e) & 3)]
#pragma unroll
        for (int e = 0; e < 16; e++) z[e] = XX(e) * fmaf(XX(e) * XX(e), 0.035677408f, 0.79788456f);
#pragma unroll
        for (int e = 0; e < 16; e++) asm("tanh.approx.f32 %0, %0;" : "+f"(z[e]));
#pragma unroll
        for (int e = 0; e < 16; e++) z[e] = fmaf(XX(e), z[e], XX(e));
#undef XX
#pragma unroll
        for (int r = 0; r < 2; r++)
            *(uint4*)(hp + (size_t)(r * 8) * FF + i4 * 32) = make_uint4(pack_bf16(z[2 * r], z[2 * r + 1]), pack_bf16(z[4 + 2 * r], z[5 + 2 * r]),
                                                                         pack_bf16(z[8 + 2 * r], z[9 + 2 * r]), pack_bf16(z[12 + 2 * r], z[13 + 2 * r]));
    }
}
__device__ __forceinline__ void job_epilogue(float* acc0, float* acc1, int q, int warp, int g, int t) {
    __nv_bfloat16* hp = g_h + (size_t)(cta_m() * 128 + warp * 16 + g) * FF + job_chunk(job_id(q)) * 64 + t * 8;
    const uint32_t pace = 0;
    epilogue_gelu(acc0, hp, q < has_mini(), pace);
    epilogue_gelu(acc1, hp + (size_t)64 * FF, q < has_mini(), pace);
    kill<96>(acc0); kill<96>(acc1);
    bar_arrive(job_bar(q), 160);
}

__device__ __forceinline__ void epilogue_qkv(const uint32_t* vv, int rg, int g, int t, int wg) {
    const int j = cta_j();
#define V(r, i) vv[2 * (i) + (r)]
    if (wg == 2) bar_sync(14, 256);
    uint8_t* p = g_qkv + (size_t)(12 * j) * 98304 + rg * 384 + g * 16;
    const uint32_t pk0 = ((POLYMASK >> (rg & 15)) & 1) ? 0x3f803f80u : 0u, pk1 = ((POLYMASK >> ((rg + 1) & 15)) & 1) ? 0x3f803f80u : 0u;
#pragma unroll
    for (int gi = 0; gi < 3; gi++) {
        const int which = (3 * j + gi) >> 3;
        const uint32_t ea0 = which == 1 ? pk0 : (which == 2 ? 0x00003f80u : 0u), ea1 = which == 1 ? pk1 : (which == 2 ? 0x00003f80u : 0u);
        const uint32_t eb0 = which == 1 ? pk0 : 0u, eb1 = which == 1 ? pk1 : 0u;
        uint32_t mx[2] = {0u, 0u};
#pragma unroll
        for (int h = 4 * gi; h < 4 * gi + 4; h++) {
#pragma unroll
            for (int c = 0; c < 2; c++) {
                const int L0 = 9 * h + 4 * c, k = L0 % 4, i0 = L0 / 4;
                const int off = h * 98304 + c * 128 + ((t - k) & 3) * 4;
                *(uint32_t*)(p + off) = (k == 0 || t >= k) ? V(0, i0) : V(0, i0 + 1);
                *(uint32_t*)(p + off + 384) = (k == 0 || t >= k) ? V(1, i0) : V(1, i0 + 1);
            }
            if (t == (9 * h + 8) % 4) {
                *(uint4*)(p + h * 98304 + 256) = make_uint4(V(0, (9 * h + 8) / 4), ea0, eb0, 0u);
                *(uint4*)(p + h * 98304 + 256 + 384) = make_uint4(V(1, (9 * h + 8) / 4), ea1, eb1, 0u);
            }
#pragma unroll
            for (int r = 0; r < 2; r++) {
                const int b0 = (9 * h) / 4;
                uint32_t a;
                asm("mul.rn.bf16x2 %0, %1, %1;" : "=r"(a) : "r"(V(r, b0)));
                asm("fma.rn.bf16x2 %0, %1, %1, %0;" : "+r"(a) : "r"(V(r, b0 + 1)));
                asm("fma.rn.bf16x2 %0, %1, %1, %0;" : "+r"(a) : "r"(V(r, b0 + 2)));
                asm("max.NaN.bf16x2 %0, %0, %1;" : "+r"(mx[r]) : "r"(a));
            }
        }
        float w0 = bf_lo(mx[0]) + bf_hi(mx[0]), w1 = bf_lo(mx[1]) + bf_hi(mx[1]);
        w0 += __shfl_xor_sync(0xffffffffu, w0, 1); w1 += __shfl_xor_sync(0xffffffffu, w1, 1);
        w0 += __shfl_xor_sync(0xffffffffu, w0, 2); w1 += __shfl_xor_sync(0xffffffffu, w1, 2);
        const uint32_t bb = __reduce_max_sync(0xffffffffu, max(__float_as_uint(w0) & 0x7fffffffu, __float_as_uint(w1) & 0x7fffffffu));
        if ((threadIdx.x & 31) == 0) asm volatile("red.shared.max.u32 [%0], %1;" :: "r"(cl(BMAX_OFF + 4 * gi)), "r"(bb) : "memory");
    }
}

__device__ __forceinline__ uint32_t exp2_fma(float a, float b, uint32_t c3f00) {
    uint32_t s, m, e, r;
    asm("prmt.b32 %0, %1, %2, 0x5410;" : "=r"(s) : "r"(__float_as_uint(a)), "r"(__float_as_uint(b)));
    asm("lop3.b32 %0, %1, 0x007f007f, %2, 0xEA;" : "=r"(m) : "r"(s), "r"(c3f00));
    asm("and.b32 %0, %1, 0xff80ff80;" : "=r"(e) : "r"(s));
    asm("fma.rn.bf16x2 %0, %1, %2, %3;" : "=r"(r) : "r"(s), "r"(m), "r"(e));
    return r;
}
template<int HALF> __device__ __forceinline__ void exps(const float* S, uint32_t* P, uint32_t c3f00) {
#pragma unroll
    for (int i = 0; i < 8; i++) {
        if ((POLYMASK >> (i + 8 * HALF)) & 1) { P[2 * i] = exp2_fma(S[4 * i], S[4 * i + 1], c3f00); P[2 * i + 1] = exp2_fma(S[4 * i + 2], S[4 * i + 3], c3f00); }
        else { P[2 * i] = pack_bf16(ex2(S[4 * i]), ex2(S[4 * i + 1])); P[2 * i + 1] = pack_bf16(ex2(S[4 * i + 2]), ex2(S[4 * i + 3])); }
    }
}
__device__ __forceinline__ void pv(float* O, const uint32_t* P, uint64_t dv) {
#pragma unroll
    for (int kk = 0; kk < 4; kk++) mma_n24_rs<1>(O, P[4 * kk], P[4 * kk + 1], P[4 * kk + 2], P[4 * kk + 3], dv + kk * (768 >> 4));
}
__device__ __forceinline__ void qk(float* S, const uint32_t* q, uint64_t dk) {
    mma_n64_rs<0>(S, q[0], q[1], q[2], q[3], dk);
    mma_n64_rs<1>(S, q[4], q[5], q[6], q[7], dk + (256 >> 4));
}
__device__ __forceinline__ int helper_id() {
    const int j = cta_j(), h = cta_m() + 16 * (7 - j);
    return (blockIdx.x < 128 && j >= 6 && h < 4 * XS) ? h : -1;
}
__device__ __forceinline__ int num_tasks() { return blockIdx.x >= 128 ? 32 - XS : (helper_id() >= 0 ? 25 : 24); }
__device__ __forceinline__ void seg_info(int seg, int& rd, int& s0, int& len) {
    const int h = helper_id();
    rd = cta_aidx() + NACTA * (h >= 0 && seg > 0 ? seg - 1 : seg); s0 = 0; len = 8;
    if (h >= 0 && seg == 1) { rd = 252 + (h & 3); s0 = h >> 2; len = 1; }
    if (rd >= 252 && h < 0) { s0 = XS; len = 8 - XS; }
}
__device__ __forceinline__ void kv_load(int task) {
    int seg = task >> 3, k = task & 7;
    if (helper_id() >= 0 && task >= 8) { seg = task == 8 ? 1 : 1 + ((task - 1) >> 3); k = task == 8 ? 0 : (task - 1) & 7; }
    int rd, s0, len; seg_info(seg, rd, s0, len);
    const int sl = task & 7;
    const uint8_t* src = g_qkv + (size_t)(rd >> 3) * 98304;
    bulk_load(KV_OFF + sl * 24576, src + 32 * 98304 + (s0 + k) * 12288, 12288, BAR_FULLKV + 8 * sl, k == 0 ? 36864 : 24576);
    bulk_load(KV_OFF + sl * 24576 + 12288, src + 64 * 98304 + (s0 + k) * 12288, 12288, BAR_FULLKV + 8 * sl, 0);
    if (k == 0) bulk_load((seg & 1) ? Q2_OFF : Q_OFF, src + (rd & 7) * 12288, 12288, BAR_FULLKV + 8 * sl, 0);
}
__device__ __forceinline__ void kv_refill(int task, int wg) {
    const int r = task + 8 - KVLAG;
    if ((r & 3) == wg && r >= 8 && r < num_tasks()) {
        mbar_wait(BAR_EMPTYKV + 8 * (r & 7), ((r >> 3) & 1) ^ 1);
        kv_load(r);
    }
}
__device__ __forceinline__ void publish(unsigned* flag, int wg, unsigned tag, bool elect) {
    bar_sync(4 + wg, 128);
    if (elect) st_release(flag, tag);
}

__device__ __forceinline__ void attention(int wg, unsigned tag) {
    const int lane = threadIdx.x & 31, t = lane & 3;
    const int warp = __shfl_sync(0xffffffffu, (threadIdx.x >> 5) & 3, 0);
    const bool elect = (threadIdx.x & 127) == 0;
    constexpr uint64_t dk0 = mkdesc(KV_OFF, 128, 384, 0), dv0 = mkdesc(KV_OFF + 12288, 384, 128, 0);
    const uint32_t zero = (blockIdx.x >> 20) * lane;
    const uint32_t c3f00 = __shfl_sync(0xffffffffu, 0x3f003f00u + zero, 0);
    unsigned* pending = nullptr;
    int T = 0;
#pragma unroll 1
    for (int seg = 0; T < num_tasks(); seg++) {
        int rd, s0, len; seg_info(seg, rd, s0, len);
        const int Tend = T + len;
        mbar_wait(BAR_FULLKV + 8 * (T & 7), (T >> 3) & 1);
        const bool fast = (__shfl_sync(0xffffffffu, lds32(FAST_OFF), 0) >> (rd >> 5)) & 1;
        const uint32_t qa = ((seg & 1) ? Q2_OFF : Q_OFF) + (wg * 8 + warp * 2) * 384 + lane * 4;
        uint32_t q[8];
        q[0] = lds32(qa); q[1] = lds32(qa + 384); q[2] = lds32(qa + 128); q[3] = lds32(qa + 384 + 128);
        q[4] = lds32(qa + 256); q[5] = lds32(qa + 384 + 256);
        if (fast && t == 1) q[4] = q[5] = 0x42fe47c0u;
        if (fast && t == 2) q[4] = q[5] = 0x3b80bf16u;
        q[6] = __shfl_sync(0xffffffffu, zero, 0); q[7] = __shfl_sync(0xffffffffu, zero, 1);
        float m0 = 0.f, m1 = 0.f;
        float SA[32], SB_[32], O[12];
        uint32_t P[16];
#pragma unroll
        for (int i = 0; i < 12; i++) O[i] = 0.f;
        if (!fast) m0 = m1 = -INFINITY;
        if (len != 8 && len != 1) {
            int n = 0;
            while (!__all_sync(0xffffffffu, ld_acquire(&g_pflag[((rd - 252) * 4 + wg) * 8 + lane % XS]) == tag))
                asm volatile("{\n.reg .pred q;\nnanosleep.u32 100;\nsetp.gt.u32 q, %0, 4000000;\n@q trap;\n}" :: "r"(++n));
#pragma unroll 2
            for (int i = 0; i < XS; i++) {
                const float4* pp = g_part + ((rd - 252) * XS + i) * 2048 + threadIdx.x;
                const float4 a = __ldcg(pp), b = __ldcg(pp + 512), c = __ldcg(pp + 1024), m = __ldcg(pp + 1536);
                const float n0 = fmaxf(m0, m.x), n1 = fmaxf(m1, m.y);
                const float f0 = ex2(m0 - n0), f1 = ex2(m1 - n1), g0 = ex2(m.x - n0), g1 = ex2(m.y - n1);
                m0 = n0; m1 = n1;
                O[0] = O[0] * f0 + a.x * g0; O[1] = O[1] * f0 + a.y * g0; O[2] = O[2] * f1 + a.z * g1; O[3] = O[3] * f1 + a.w * g1;
                O[4] = O[4] * f0 + b.x * g0; O[5] = O[5] * f0 + b.y * g0; O[6] = O[6] * f1 + b.z * g1; O[7] = O[7] * f1 + b.w * g1;
                O[8] = O[8] * f0 + c.x * g0; O[9] = O[9] * f0 + c.y * g0; O[10] = O[10] * f1 + c.z * g1; O[11] = O[11] * f1 + c.w * g1;
            }
        }
#pragma unroll
        for (int i = 0; i < 12; i++) asm volatile("add.f32 %0, %0, %1;" : "+f"(O[i]) : "f"(__uint_as_float(q[6])) : "memory");
        keep<8>(q);
        if (fast) {
            WG_FENCE();
            qk(SA, q, dk0 + (uint64_t)((T & 7) * (24576 >> 4))); WG_COMMIT();
            qk(SB_, q, dk0 + (uint64_t)((T & 7) * (24576 >> 4) + (3072 >> 4))); WG_COMMIT();
            bool started = false;
#pragma unroll 1
            for (; T < Tend; T++) {
                const bool more = T + 1 < Tend;
                const uint64_t so = (uint64_t)((T & 7) * (24576 >> 4));
                const uint64_t dk = dk0 + so, dv = dv0 + so, dkn = dk0 + (uint64_t)(((more ? T + 1 : T) & 7) * (24576 >> 4));
#pragma unroll
                for (int h = 0; h < 4; h++) {
                    float* S = (h & 1) ? SB_ : SA;
                    WG_WAIT(1);
                    keep<32>(S); keep<12>(O);
                    if (h == 0 && elect && started) mbar_arrive(BAR_EMPTYKV + 8 * ((T - 1) & 7));
                    if (h & 1) exps<1>(S, P, c3f00); else exps<0>(S, P, c3f00);
                    keep<16>(P);
                    WG_FENCE();
                    pv(O, P, dv + h * (3072 >> 4)); WG_COMMIT();
                    qk(S, q, h < 2 ? dk + (h + 2) * (3072 >> 4) : dkn + (h - 2) * (3072 >> 4)); WG_COMMIT();
                    if (h == 1 && more) mbar_wait(BAR_FULLKV + 8 * ((T + 1) & 7), ((T + 1) >> 3) & 1);
                    if (h == 0 && warp == 1) kv_refill(T, wg);
                    if (h == 2 && !started && seg > 0) publish(pending, wg, tag, elect);
                }
                started = true;
            }
            WG_WAIT(0);
            keep<12>(O); keep<32>(SA); keep<32>(SB_);
            m0 = m1 = 0.f;
        } else {
            if (seg > 0) publish(pending, wg, tag, elect);
#pragma unroll 1
            for (; T < Tend; T++) {
                if (warp == 1) kv_refill(T, wg);
                mbar_wait(BAR_FULLKV + 8 * (T & 7), (T >> 3) & 1);
#pragma unroll 1
                for (int h = 0; h < 4; h++) {
                    const uint64_t so = (uint64_t)(((T & 7) * 24576 + h * 3072) >> 4);
                    WG_FENCE();
                    qk(SA, q, dk0 + so); WG_COMMIT();
                    WG_WAIT(0);
                    keep<32>(SA); keep<12>(O);
                    float n0 = m0, n1 = m1;
#pragma unroll
                    for (int i = 0; i < 8; i++) { n0 = fmaxf(n0, fmaxf(SA[4 * i], SA[4 * i + 1])); n1 = fmaxf(n1, fmaxf(SA[4 * i + 2], SA[4 * i + 3])); }
                    n0 = fmaxf(n0, __shfl_xor_sync(0xffffffffu, n0, 1)); n0 = fmaxf(n0, __shfl_xor_sync(0xffffffffu, n0, 2));
                    n1 = fmaxf(n1, __shfl_xor_sync(0xffffffffu, n1, 1)); n1 = fmaxf(n1, __shfl_xor_sync(0xffffffffu, n1, 2));
                    const float f0 = ex2(m0 - n0), f1 = ex2(m1 - n1);
                    m0 = n0; m1 = n1;
#pragma unroll
                    for (int i = 0; i < 3; i++) { O[4 * i] *= f0; O[4 * i + 1] *= f0; O[4 * i + 2] *= f1; O[4 * i + 3] *= f1; }
#pragma unroll
                    for (int i = 0; i < 8; i++) {
                        P[2 * i] = pack_bf16(ex2(SA[4 * i] - m0), ex2(SA[4 * i + 1] - m0));
                        P[2 * i + 1] = pack_bf16(ex2(SA[4 * i + 2] - m1), ex2(SA[4 * i + 3] - m1));
                    }
                    keep<16>(P); keep<12>(O);
                    WG_FENCE();
                    pv(O, P, dv0 + so); WG_COMMIT();
                    WG_WAIT(0);
                    keep<12>(O);
                }
                if (elect && T + 1 < Tend) mbar_arrive(BAR_EMPTYKV + 8 * (T & 7));
            }
        }
        if (elect) mbar_arrive(BAR_EMPTYKV + 8 * ((T - 1) & 7));
        if (wg == 1) TS2(4 + seg);
        if (len == 1) {
            float4* pp = g_part + ((rd - 252) * XS + s0) * 2048 + threadIdx.x;
            pp[0] = make_float4(O[0], O[1], O[2], O[3]); pp[512] = make_float4(O[4], O[5], O[6], O[7]);
            pp[1024] = make_float4(O[8], O[9], O[10], O[11]); pp[1536] = make_float4(m0, m1, 0.f, 0.f);
            pending = &g_pflag[((rd - 252) * 4 + wg) * 8 + s0];
            continue;
        }
        const int head = rd >> 3, rb = (rd & 7) * 4 + wg, g = lane >> 2;
        const float l0 = __shfl_sync(0xffffffffu, O[8], (lane & ~3) | 1), l1 = __shfl_sync(0xffffffffu, O[10], (lane & ~3) | 1);
        const float r0 = __frcp_rn(l0), r1 = __frcp_rn(l1);
        uint8_t* ob = g_o + (size_t)(rb >> 1) * (9 * 16384) + ((rb & 1) * 8 + warp * 2) * 1024 + g * 16;
        uint8_t* op = ob + (head >> 2) * 16384 + (head & 3) * 256 + t * 4;
#pragma unroll
        for (int i = 0; i < 2; i++) {
            *(uint32_t*)(op + i * 128) = pack_bf16(O[4 * i] * r0, O[4 * i + 1] * r0);
            *(uint32_t*)(op + i * 128 + 1024) = pack_bf16(O[4 * i + 2] * r1, O[4 * i + 3] * r1);
        }
        if (t == 0) {
            uint8_t* ol = ob + 8 * 16384 + (head >> 2) * 128 + (head & 3) * 4;
            *(uint32_t*)ol = pack_bf16(O[8] * r0, O[9] * r0); *(uint32_t*)(ol + 1024) = pack_bf16(O[10] * r1, O[11] * r1);
        }
        pending = &g_oflag[rb * 32 + head];
    }
    publish(pending, wg, tag, elect);
}

__global__ void __cluster_dims__(2, 1, 1) __launch_bounds__(NTHREADS, 1) fused_kernel(const __grid_constant__ Params p) {
    extern __shared__ __align__(1024) uint8_t smem_raw[];
    if ((uint32_t)__cvta_generic_to_shared(smem_raw) != cl(SB)) asm volatile("trap;");
    const int wg = __shfl_sync(0xffffffffu, threadIdx.x >> 7, 0);
    const int lane = threadIdx.x & 31;
    const bool elect = (threadIdx.x & 127) == 0;
    const bool gemm = blockIdx.x < 128;
    const bool five = cta_j() == 2 || cta_j() == 5;
    if (threadIdx.x >= 32 && threadIdx.x < 42) asm volatile("prefetch.tensormap [%0];" :: "l"(&p.x + (threadIdx.x - 32)) : "memory");
    const int lrow = (blockIdx.x & 1) * 64 + (threadIdx.x >> 3);
    uint32_t v[36];
    if (gemm) {
        const uint4* xr = (const uint4*)(p.xp + (size_t)(cta_m() * 128 + lrow) * DM) + (lane & 7);
#pragma unroll
        for (int i = 0; i < 9; i++) { const uint4 w = __ldg(xr + i * 8); v[4 * i] = w.x; v[4 * i + 1] = w.y; v[4 * i + 2] = w.z; v[4 * i + 3] = w.w; }
        if ((threadIdx.x >> 5) == 5) l2_prefetch((const uint8_t*)p.wqkvp + blockIdx.x * 15616, blockIdx.x == 127 ? 7424 : 15616, 0);
    }
    if ((threadIdx.x & 31) < NBARS / 16) {
        const int i = (threadIdx.x >> 5) * (NBARS / 16) + (threadIdx.x & 31);
        const uint32_t cnt = (i >= 55 && i < 64) || i == 79 ? 2 : (i >= 38 && i < 46 ? 4 : 1);
        mbar_init(BAR_OFF + 8 * i, cnt);
        asm volatile("fence.mbarrier_init.release.cluster;" ::: "memory");
    }
    if (threadIdx.x >= 40 && threadIdx.x < 43) asm volatile("st.shared.u32 [%0], %1;" :: "r"(cl(BMAX_OFF + 4 * (threadIdx.x - 40))), "r"(0) : "memory");
    __syncthreads();
    asm volatile("barrier.cluster.arrive.relaxed.aligned;" ::: "memory");
    TS(wg);
    if (gemm) {
        if (threadIdx.x < 32) {
#pragma unroll 1
            for (int ks = 0; ks < (five ? 7 : 9); ks++)
                tma3d(B_OFF + ks * (five ? 10240 : 8192), five ? &p.wq5 : &p.wq4, ks * 16, (216 * cta_j()) >> 6, BAR_FULLW + 8 * ks, five ? 10240 : 8192);
        }
        float f[72], s = 0.f, s2 = 0.f;
#pragma unroll
        for (int i = 0; i < 36; i++) { f[2 * i] = bf_lo(v[i]); f[2 * i + 1] = bf_hi(v[i]); s += f[2 * i]; s2 += f[2 * i + 1]; }
        s += s2;
        s += __shfl_xor_sync(0xffffffffu, s, 1); s += __shfl_xor_sync(0xffffffffu, s, 2); s += __shfl_xor_sync(0xffffffffu, s, 4);
        const float mean = s * (1.0f / DM);
        if (wg == 1) TS(29);
        float q = 0.f, q2 = 0.f;
#pragma unroll
        for (int i = 0; i < 36; i++) { f[2 * i] -= mean; f[2 * i + 1] -= mean; q = fmaf(f[2 * i], f[2 * i], q); q2 = fmaf(f[2 * i + 1], f[2 * i + 1], q2); }
        q += q2;
        q += __shfl_xor_sync(0xffffffffu, q, 1); q += __shfl_xor_sync(0xffffffffu, q, 2); q += __shfl_xor_sync(0xffffffffu, q, 4);
        const float rstd = rsqrtf(q * (1.0f / DM) + 1e-5f);
        const uint32_t dst = cl(A_OFF + lrow * 128 + (((lane & 7) ^ (lrow & 7)) << 4));
#pragma unroll
        for (int i = 0; i < 9; i++)
            asm volatile("st.shared.v4.b32 [%0], {%1,%2,%3,%4};" :: "r"(dst + i * 16384),
                "r"(pack_bf16(f[8 * i] * rstd, f[8 * i + 1] * rstd)), "r"(pack_bf16(f[8 * i + 2] * rstd, f[8 * i + 3] * rstd)),
                "r"(pack_bf16(f[8 * i + 4] * rstd, f[8 * i + 5] * rstd)), "r"(pack_bf16(f[8 * i + 6] * rstd, f[8 * i + 7] * rstd)) : "memory");
        if (wg == 1) TS(31);
        asm volatile("fence.proxy.async.shared::cta;" ::: "memory");
    }
    asm volatile("barrier.cluster.wait.aligned;" ::: "memory");
    __syncthreads();
    TS(28);

    if (wg == 0) {
        asm volatile("setmaxnreg.dec.sync.aligned.u32 24;");
        const int warp = __shfl_sync(0xffffffffu, threadIdx.x >> 5, 0);
        if (warp == 0) {
            if (gemm) {
                int st = 0; uint32_t ph = 0;
                const int nst = five ? 7 : 9; const uint32_t sb = five ? 10240 : 8192;
                send_half(0); send_half(1);
#pragma unroll 1
                for (int ks = nst; ks < 36; ks++) {
                    const int i = ks - nst;
                    if ((i % 3) == 0 && i < 21) send_half(2 + i / 3);
                    mbar_wait(BAR_EMPTYW + 8 * st, ph);
                    tma3d(B_OFF + st * sb, five ? &p.wq5 : &p.wq4, ks * 16, (216 * cta_j()) >> 6, BAR_FULLW + 8 * st, sb);
                    if (++st == nst) { st = 0; ph ^= 1; }
                }
                st = 0; ph = 1;
                mbar_wait(BAR_WDONE, 0);
#pragma unroll 1
                for (int q = 0; q < num_jobs(); q++) {
#pragma unroll 1
                    for (int k = 0; k < DM; k += (q < has_mini() ? 96 : 32)) {
                        mbar_wait(BAR_EMPTYB + 8 * st, ph);
                        tma3d(B_OFF + st * 12288, q < has_mini() ? &p.w1n : &p.w1, k, job_chunk(job_id(q)), BAR_FULLB + 8 * st, 12288);
                        if (++st == 6) { st = 0; ph ^= 1; }
                    }
                }
                if (cta_isG()) {
#pragma unroll 1
                    for (int hk = 0; hk < 162; hk++) {
                        mbar_wait(BAR_EMPTYB + 8 * st, ph);
                        if (hk < 144) tma5d(B_OFF + st * 12288, &p.w2, (hk >> 1) * 32 + (hk & 1) * 4, cta_j() * 3, BAR_FULLB + 8 * st, 12288);
                        else tma4d(B_OFF + st * 12288, hk < 160 ? &p.wo : &p.wol, hk < 160 ? 0 : 16, hk < 160 ? (hk - 144) * 2 : (hk - 160) * 16, cta_j() * 3, BAR_FULLB + 8 * st, 12288);
                        if (++st == 6) { st = 0; ph ^= 1; }
                    }
                }
            }
        } else if (warp == 1) {
            if (gemm) {
                const unsigned tag = get_tag();
                bar_sync(10, 288);
                if (lane < 3) atomicMax(&g_bound[(3 * cta_j() + lane) * 16], ((unsigned long long)tag << 32) | lds32(BMAX_OFF + 4 * lane));
                __syncwarp();
                if (lane == 0) red_release(&g_qkvcnt, 1);
                __syncwarp();
#pragma unroll 1
                for (int q = 0; q < num_jobs(); q++) {
                    bar_sync(job_bar(q), 160);
                    if (lane == 0) st_release(&g_hflag[cta_m() * 32 + job_id(q)], tag);
                    __syncwarp();
                }
            }
        } else if (warp == 3) {
            if (cta_isG()) {
                int sa = 0, dep = 0, next_dep = 0; uint32_t pa = 0;
#pragma unroll 1
                for (int kk = 0; kk < 84; kk++) {
                    if (kk == next_dep) {
                        mbar_wait(BAR_DEP + 8 * dep, 0);
                        dep++;
                        next_dep = kk < 63 ? (kk == 0 ? 30 : (kk == 30 ? 54 : 63)) : (kk == 63 ? 75 : kk + 1);
                    }
                    mbar_wait(BAR_EMPTYA + 8 * sa, pa);
                    if (kk < 75) tma2d(A_OFF + sa * 16384, kk < 72 ? &p.h : &p.x, (kk < 72 ? kk : 3 * cta_j() + kk - 72) * 64, cta_m() * 128, BAR_FULLA + 8 * sa, 16384);
                    else bulk_load(A_OFF + sa * 16384, g_o + (size_t)(cta_m() * 9 + (kk - 75)) * 16384, 16384, BAR_FULLA + 8 * sa, 16384);
                    if (++sa == 9) { sa = 0; pa ^= 1; }
                }
            } else {
                const unsigned tag = get_tag();
                if (gemm) mbar_wait(BAR_WDONE, 0);
                flag_wait(&g_qkvcnt, tag * 128);
                __syncwarp();
                const float bn = lane < 24 ? __uint_as_float((uint32_t)ld_tagged(&g_bound[lane * 16])) * 1.02f : 0.f;
                asm volatile("fence.proxy.async.global;" ::: "memory");
                const float bk = __shfl_sync(0xffffffffu, bn, (lane & 7) + 8), bv = __shfl_sync(0xffffffffu, bn, (lane & 7) + 16);
                const uint32_t fastmask = __ballot_sync(0xffffffffu, __fsqrt_rn(bn * bk) + 0.5f * __log2f(fmaxf(bv, 1.0f)) <= 100.0f);
                asm volatile("st.shared.u32 [%0], %1;" :: "r"(cl(FAST_OFF)), "r"(fastmask) : "memory");
#pragma unroll 1
                for (int s = 0; s < 8; s++) {
                    if (gemm) mbar_wait(BAR_EMPTYA + 8 * (s < 4 ? (3 * s + 4) >> 1 : 8), 0);
                    kv_load(s);
                }
            }
        } else {
            if (gemm) l2_prefetch((const uint8_t*)p.w1p + blockIdx.x * 41472, 41472, 300);
            else {
                asm volatile("nanosleep.u32 4000;");
#pragma unroll 1
                for (int i = 0; i < 36; i++) {
                    if (i < 32) l2_prefetch_bulk((const uint8_t*)p.w2p + (i * 4 + (blockIdx.x - 128)) * 41472, 41472);
                    else l2_prefetch_bulk((const uint8_t*)p.wop + ((i - 32) * 4 + (blockIdx.x - 128)) * 41472, 41472);
                }
            }
            if (cta_isG()) {
                const unsigned tag = get_tag();
                mbar_wait(BAR_WDONE, 0);
#pragma unroll 1
                for (int d = 0; d < 4; d++) {
                    if (lane < (d == 0 ? 14 : 19 + 3 * d)) flag_wait(&g_hflag[cta_m() * 32 + lane], tag);
                    __syncwarp();
                    fence_async();
                    if (lane == 0) mbar_arrive(BAR_DEP + 8 * d);
                }
                int d = 0, n = 0;
                const unsigned* f0 = &g_oflag[(cta_m() * 2) * 32 + lane];
#pragma unroll 1
                while (d < 9) {
                    unsigned a, b;
                    asm volatile("ld.acquire.gpu.global.u32 %0, [%1];" : "=r"(a) : "l"(f0) : "memory");
                    asm volatile("ld.acquire.gpu.global.u32 %0, [%1];" : "=r"(b) : "l"(f0 + 32) : "memory");
                    const uint32_t miss = ~__ballot_sync(0xffffffffu, a == tag && b == tag);
                    const int ready = miss ? (__ffs(miss) - 1) >> 2 : 9;
                    if (ready > d) {
                        fence_async();
                        if (lane >= d && lane < ready) mbar_arrive(BAR_DEP + 8 * (4 + lane));
                        d = ready;
                    } else asm volatile("{\n.reg .pred q;\nnanosleep.u32 200;\nsetp.gt.u32 q, %0, 4000000;\n@q trap;\n}" :: "r"(++n));
                }
            }
        }
        if (cta_isG()) {
            bar_sync(4, 128);
            if (elect) red_relaxed(&g_done, 1);
            return;
        }
        bar_sync(2, 256);
        asm volatile("setmaxnreg.inc.sync.aligned.u32 128;");
    } else if (wg == 3) {
        asm volatile("setmaxnreg.dec.sync.aligned.u32 24;");
        if (gemm) {
            const int tid = threadIdx.x & 127;
#pragma unroll 2
            for (int w = tid; w < 992; w += 128) {
                uint32_t bw, bdst;
                if (w < 768) {
                    const int c = w >> 8, r = (w >> 5) & 7, k = w & 31;
                    bw = (r < num_jobs() && (r >= has_mini() || c < 1)) ? __ldg((const uint32_t*)p.b1p + (job_chunk(job_id(r)) + c) * 32 + k) : 0u;
                    bdst = BIAS_OFF + c * 1024 + r * 128 + (((k >> 2) ^ r) << 4) + (k & 3) * 4;
                } else {
                    const int u = w - 768, q = u >> 5, k = u & 3;
                    bw = (q < 5 && k == (q >> 1)) ? ((q & 1) ? 0x3f800000u : 0x00003f80u) : 0u;
                    bdst = ONE_OFF + u * 4;
                }
                asm volatile("st.shared.u32 [%0], %1;" :: "r"(cl(bdst)), "r"(bw) : "memory");
            }
            if (cta_isG() && tid < 96) {
                const uint32_t b = __ldg((const uint32_t*)(p.b2p + cta_j() * 192) + tid);
                asm volatile("st.shared.v2.f32 [%0], {%1, %2};" :: "r"(cl(B2_OFF + 8 * tid)), "f"(bf_lo(b)), "f"(bf_hi(b)) : "memory");
            }
            asm volatile("fence.proxy.async.shared::cta;" ::: "memory");
            bar_sync(7, 128);
            if (elect) mbar_arrive(BAR_INFO);
        }
        if (cta_isG()) {
            if (elect) red_relaxed(&g_done, 1);
            return;
        }
        bar_sync(1, 256);
        asm volatile("setmaxnreg.inc.sync.aligned.u32 128;");
    } else {
        const int warp = __shfl_sync(0xffffffffu, (threadIdx.x >> 5) & 3, 0), g = lane >> 2, t = lane & 3;
        asm volatile("setmaxnreg.inc.sync.aligned.u32 232;");
        if (gemm) {
            uint32_t vv[54];
            switch (cta_j()) {
                case 0: qkv_mainloop<0>(vv, wg, elect); break;
                case 1: qkv_mainloop<1>(vv, wg, elect); break;
                case 2: qkv_mainloop<2>(vv, wg, elect); break;
                case 3: qkv_mainloop<3>(vv, wg, elect); break;
                case 4: qkv_mainloop<4>(vv, wg, elect); break;
                case 5: qkv_mainloop<5>(vv, wg, elect); break;
                case 6: qkv_mainloop<6>(vv, wg, elect); break;
                default: qkv_mainloop<7>(vv, wg, elect); break;
            }
            if (wg == 1) TS(26);
            epilogue_qkv(vv, cta_m() * 16 + (wg - 1) * 8 + warp * 2, g, t, wg);
            if (wg == 1) bar_arrive(14, 256);
            if (wg == 1) TS(27);
            bar_arrive(10, 288);
        }
        if (gemm) {
            float acc0[96], acc1[96];
            kill<96>(acc0); kill<96>(acc1);
            mbar_wait(BAR_INFO, 0);
#pragma unroll 1
            for (int q = wg - 1; q < num_jobs() + cta_isG(); q += 2) {
                const bool g2 = q == num_jobs();
                const uint32_t xa = A_OFF + (warp * 16 + (lane & 15)) * 128 + (((lane >> 4) ^ (lane & 7)) << 4);
                if (g2) TS2(9);
                if (q < has_mini()) mini_mainloop(acc0, acc1, elect); else job_mainloop(acc0, acc1, q, g2, xa, t, wg, elect);
                if (g2) {
                    TS2(12);
#pragma unroll
                    for (int c = 0; c < 3; c++) {
#pragma unroll
                        for (int i2 = 4 * c; i2 < 4 * c + 4; i2++) {
#pragma unroll
                            for (int mh = 0; mh < 2; mh++) {
                                const float* a = (mh ? acc1 : acc0) + 8 * i2;
                                asm volatile("stmatrix.sync.aligned.m8n8.x4.shared.b16 [%0], {%1,%2,%3,%4};"
                                    :: "r"(cl((xa ^ ((i2 & 3) << 5)) + (3 + c) * 16384 + mh * 8192)),
                                       "r"(pack_bf16(a[0], a[1])), "r"(pack_bf16(a[2], a[3])), "r"(pack_bf16(a[4], a[5])), "r"(pack_bf16(a[6], a[7])) : "memory");
                            }
                        }
                        asm volatile("fence.proxy.async.shared::cta;" ::: "memory");
                        bar_sync(4 + wg, 128);
                        if (elect) asm volatile("cp.async.bulk.tensor.2d.global.shared::cta.bulk_group [%0, {%1, %2}], [%3];"
                                        :: "l"(&p.outm), "r"(cta_j() * 192 + c * 64), "r"(cta_m() * 128), "r"(cl(A_OFF + (3 + c) * 16384)) : "memory");
                    }
                    if (elect) asm volatile("cp.async.bulk.commit_group;\ncp.async.bulk.wait_group.read 0;" ::: "memory");
                    TS2(14);
                    break;
                }
                TS(17 + (q < 4 ? q : 4));
                job_epilogue(acc0, acc1, q, warp, g, t);
                TS(22 + (q < 3 ? q : 3));
            }
        }
        if (cta_isG()) {
            bar_sync(4 + wg, 128);
            if (elect) red_relaxed(&g_done, 1);
            return;
        }
        asm volatile("setmaxnreg.dec.sync.aligned.u32 128;");
        bar_arrive(3 - wg, 256);
    }
    __syncwarp();
    TS2(8 + wg);
    attention(wg, get_tag());
    TS2(12 + wg);
    bar_sync(4 + wg, 128);
    if (elect) red_relaxed(&g_done, 1);
}

typedef CUresult (*EncFn)(CUtensorMap*, CUtensorMapDataType, cuuint32_t, void*, const cuuint64_t*, const cuuint64_t*, const cuuint32_t*,
                          const cuuint32_t*, CUtensorMapInterleave, CUtensorMapSwizzle, CUtensorMapL2promotion, CUtensorMapFloatOOBfill);

void make_map(EncFn enc, CUtensorMap* m, const void* ptr, int rank, const cuuint64_t* dims, const cuuint64_t* strides, const cuuint32_t* box) {
    cuuint32_t es[5] = {1, 1, 1, 1, 1};
    enc(m, CU_TENSOR_MAP_DATA_TYPE_BFLOAT16, rank, const_cast<void*>(ptr), dims, strides, box, es, CU_TENSOR_MAP_INTERLEAVE_NONE,
        CU_TENSOR_MAP_SWIZZLE_128B, L2PROMO, CU_TENSOR_MAP_FLOAT_OOB_FILL_NONE);
}
void make_act_map(EncFn enc, CUtensorMap* m, const void* ptr, int cols) {
    cuuint64_t d[2] = {(cuuint64_t)cols, SEQ}, s[1] = {(cuuint64_t)cols * 2}; cuuint32_t b[2] = {64, 128};
    make_map(enc, m, ptr, 2, d, s, b);
}

}

extern "C" void kernel_launch(void* const* d_in, const int* in_sizes, int n_in, void* d_out, int out_size) {
    static Params prm;
    static bool ready = false;
    static const void* key[9];
    bool same = ready && key[8] == d_out;
    for (int i = 0; i < 8 && same; i++) same = key[i] == d_in[i];
    if (!same) {
        EncFn enc = nullptr; cudaDriverEntryPointQueryResult qr;
        cudaGetDriverEntryPoint("cuTensorMapEncodeTiled", (void**)&enc, cudaEnableDefault, &qr);
        void* hp;
        cudaGetSymbolAddress(&hp, g_h);
        make_act_map(enc, &prm.x, d_in[0], DM);
        make_act_map(enc, &prm.h, hp, FF);
        make_act_map(enc, &prm.outm, d_out, DM);
        {
            cuuint64_t d[3] = {64, DM, 27}, s[2] = {1728 * 2, 128}; cuuint32_t b4[3] = {64, 16, 4}, b5[3] = {64, 16, 5};
            make_map(enc, &prm.wq4, d_in[1], 3, d, s, b4);
            make_map(enc, &prm.wq5, d_in[1], 3, d, s, b5);
        }
        {
            cuuint64_t d[3] = {64, DM, FF / 64}, s[2] = {FF * 2, 128}; cuuint32_t b[3] = {64, 32, 3};
            make_map(enc, &prm.w1, d_in[4], 3, d, s, b);
            cuuint32_t bn[3] = {64, 96, 1};
            make_map(enc, &prm.w1n, d_in[4], 3, d, s, bn);
        }
        {
            cuuint64_t d[4] = {64, 18, NH, DM / 64}, s[3] = {DM * 2, 18 * DM * 2, 128}; cuuint32_t b0[4] = {64, 16, 2, 3}, b1[4] = {64, 2, 16, 3};
            make_map(enc, &prm.wo, d_in[2], 4, d, s, b0);
            make_map(enc, &prm.wol, d_in[2], 4, d, s, b1);
        }
        {
            cuuint64_t d[5] = {64, 2, 4, 2280, DM / 64}, s[4] = {DM * 2, 16 * DM * 2, 2 * DM * 2, 128}; cuuint32_t b[5] = {64, 2, 4, 4, 3};
            make_map(enc, &prm.w2, d_in[6], 5, d, s, b);
        }
        prm.xp = (const __nv_bfloat16*)d_in[0]; prm.wqkvp = (const __nv_bfloat16*)d_in[1]; prm.w1p = (const __nv_bfloat16*)d_in[4];
        prm.b1p = (const __nv_bfloat16*)d_in[5]; prm.b2p = (const __nv_bfloat16*)d_in[7]; prm.out = (__nv_bfloat16*)d_out;
        prm.w2p = (const __nv_bfloat16*)d_in[6]; prm.wop = (const __nv_bfloat16*)d_in[2];
        cudaFuncSetAttribute(fused_kernel, cudaFuncAttributeMaxDynamicSharedMemorySize, SMEM_BYTES);
        for (int i = 0; i < 8; i++) key[i] = d_in[i];
        key[8] = d_out; ready = true;
    }
    fused_kernel<<<NCTA, NTHREADS, SMEM_BYTES, cudaStreamPerThread>>>(prm);
}
```

```cpp
#include <cuda_runtime.h>
#include <cuda_bf16.h>
#include <cuda.h>
#include <stdint.h>

#define L2PROMO CU_TENSOR_MAP_L2_PROMOTION_L2_128B
namespace {

constexpr int SEQ = 2048, DM = 576, FF = 4608, NH = 32;
constexpr int NCTA = 132, NTHREADS = 512, NACTA = 84;
#define GUARD 80.0f
#define KVLAG 5
#define PMASK 0xAD6Bu
constexpr uint32_t POLYMASK = PMASK;

constexpr uint32_t SB = 0x400;
constexpr uint32_t A_OFF = SB;
constexpr uint32_t B_OFF = SB + 9 * 16384;
constexpr uint32_t Q_OFF = SB, Q2_OFF = SB + 12288 + 8 * 24576;
constexpr uint32_t K_OFF = SB + 12288, V_OFF = K_OFF + 8 * 12288;
constexpr uint32_t BAR_OFF = B_OFF + 6 * 12288;
constexpr uint32_t BAR_FULLA = BAR_OFF, BAR_EMPTYA = BAR_FULLA + 72, BAR_FULLB = BAR_EMPTYA + 72, BAR_EMPTYB = BAR_FULLB + 48,
                   BAR_FULLKV = BAR_EMPTYB + 48, BAR_EMPTYKV = BAR_FULLKV + 64, BAR_FULLW = BAR_EMPTYKV + 64, BAR_EMPTYW = BAR_FULLW + 72,
                   BAR_INFO = BAR_EMPTYW + 72, BAR_DEP = BAR_INFO + 16, BAR_WDONE = BAR_DEP + 13 * 8, FAST_OFF = BAR_WDONE + 8, BMAX_OFF = FAST_OFF + 4;
constexpr int NBARS = 9 + 9 + 6 + 6 + 8 + 8 + 9 + 9 + 2 + 13 + 1;
static_assert(NBARS % 16 == 0, "barrier init");
constexpr uint32_t ONE_OFF = BAR_OFF + 768;
constexpr uint32_t BIAS_OFF = BAR_OFF + 2048;
constexpr uint32_t TASK_OFF = BIAS_OFF + 3072;
constexpr uint32_t SMEM_END = TASK_OFF + 256;
static_assert(ONE_OFF + 1024 <= BIAS_OFF && BIAS_OFF % 1024 == 0, "smem map");
constexpr uint32_t SMEM_BYTES = SMEM_END - SB;
static_assert(SMEM_BYTES <= 232448, "smem");

__device__ __align__(1024) uint8_t g_h[SEQ * FF * 2];
__device__ __align__(1024) uint8_t g_o[SEQ * DM * 2];
__device__ __align__(1024) uint8_t g_qkv[96 * 98304];
__device__ unsigned long long g_bound[24 * 16];
__device__ unsigned g_done;
__device__ unsigned g_qkvcnt;
__device__ unsigned g_hflag[16 * 32];
#define XS 6
__device__ __align__(16) float4 g_part[4 * XS * 4 * 512];
__device__ unsigned g_pflag[4 * 4 * 8];
__device__ unsigned g_oflag[32 * 32];
#define TS(i)
#define TS2(i)

struct Params {
    const __nv_bfloat16* xp; const __nv_bfloat16* wqkvp; const __nv_bfloat16* w1p; const __nv_bfloat16* b1p; const __nv_bfloat16* b2p;
    const __nv_bfloat16* w2p; const __nv_bfloat16* wop;
    __nv_bfloat16* out;
    CUtensorMap wq4, wq5, w1n, w1m, w1, w2, wo, wol, x, outm;
};

template<int N> __device__ __forceinline__ void mma_ssp(float* d, uint64_t da, uint64_t db, int sd);
template<> __device__ __forceinline__ void mma_ssp<8>(float* d, uint64_t da, uint64_t db, int sd) {
    asm volatile("{\n.reg .pred p;\nsetp.ne.b32 p, %6, 0;\nwgmma.mma_async.sync.aligned.m64n8k16.f32.bf16.bf16 {%0,%1,%2,%3}, %4, %5, p, 1, 1, 0, 1;\n}\n"
      : "+f"(d[0]),"+f"(d[1]),"+f"(d[2]),"+f"(d[3])
      : "l"(da), "l"(db), "r"(sd));
}
template<> __device__ __forceinline__ void mma_ssp<16>(float* d, uint64_t da, uint64_t db, int sd) {
    asm volatile("{\n.reg .pred p;\nsetp.ne.b32 p, %10, 0;\nwgmma.mma_async.sync.aligned.m64n16k16.f32.bf16.bf16 {%0,%1,%2,%3,%4,%5,%6,%7}, %8, %9, p, 1, 1, 0, 1;\n}\n"
      : "+f"(d[0]),"+f"(d[1]),"+f"(d[2]),"+f"(d[3]),"+f"(d[4]),"+f"(d[5]),"+f"(d[6]),"+f"(d[7])
      : "l"(da), "l"(db), "r"(sd));
}
template<> __device__ __forceinline__ void mma_ssp<24>(float* d, uint64_t da, uint64_t db, int sd) {
    asm volatile("{\n.reg .pred p;\nsetp.ne.b32 p, %14, 0;\nwgmma.mma_async.sync.aligned.m64n24k16.f32.bf16.bf16 {%0,%1,%2,%3,%4,%5,%6,%7,%8,%9,%10,%11}, %12, %13, p, 1, 1, 0, 1;\n}\n"
      : "+f"(d[0]),"+f"(d[1]),"+f"(d[2]),"+f"(d[3]),"+f"(d[4]),"+f"(d[5]),"+f"(d[6]),"+f"(d[7]),"+f"(d[8]),"+f"(d[9]),"+f"(d[10]),"+f"(d[11])
      : "l"(da), "l"(db), "r"(sd));
}
template<> __device__ __forceinline__ void mma_ssp<32>(float* d, uint64_t da, uint64_t db, int sd) {
    asm volatile("{\n.reg .pred p;\nsetp.ne.b32 p, %18, 0;\nwgmma.mma_async.sync.aligned.m64n32k16.f32.bf16.bf16 {%0,%1,%2,%3,%4,%5,%6,%7,%8,%9,%10,%11,%12,%13,%14,%15}, %16, %17, p, 1, 1, 0, 1;\n}\n"
      : "+f"(d[0]),"+f"(d[1]),"+f"(d[2]),"+f"(d[3]),"+f"(d[4]),"+f"(d[5]),"+f"(d[6]),"+f"(d[7]),"+f"(d[8]),"+f"(d[9]),"+f"(d[10]),"+f"(d[11]),"+f"(d[12]),"+f"(d[13]),"+f"(d[14]),"+f"(d[15])
      : "l"(da), "l"(db), "r"(sd));
}
template<> __device__ __forceinline__ void mma_ssp<40>(float* d, uint64_t da, uint64_t db, int sd) {
    asm volatile("{\n.reg .pred p;\nsetp.ne.b32 p, %22, 0;\nwgmma.mma_async.sync.aligned.m64n40k16.f32.bf16.bf16 {%0,%1,%2,%3,%4,%5,%6,%7,%8,%9,%10,%11,%12,%13,%14,%15,%16,%17,%18,%19}, %20, %21, p, 1, 1, 0, 1;\n}\n"
      : "+f"(d[0]),"+f"(d[1]),"+f"(d[2]),"+f"(d[3]),"+f"(d[4]),"+f"(d[5]),"+f"(d[6]),"+f"(d[7]),"+f"(d[8]),"+f"(d[9]),"+f"(d[10]),"+f"(d[11]),"+f"(d[12]),"+f"(d[13]),"+f"(d[14]),"+f"(d[15]),"+f"(d[16]),"+f"(d[17]),"+f"(d[18]),"+f"(d[19])
      : "l"(da), "l"(db), "r"(sd));
}
template<> __device__ __forceinline__ void mma_ssp<48>(float* d, uint64_t da, uint64_t db, int sd) {
    asm volatile("{\n.reg .pred p;\nsetp.ne.b32 p, %26, 0;\nwgmma.mma_async.sync.aligned.m64n48k16.f32.bf16.bf16 {%0,%1,%2,%3,%4,%5,%6,%7,%8,%9,%10,%11,%12,%13,%14,%15,%16,%17,%18,%19,%20,%21,%22,%23}, %24, %25, p, 1, 1, 0, 1;\n}\n"
      : "+f"(d[0]),"+f"(d[1]),"+f"(d[2]),"+f"(d[3]),"+f"(d[4]),"+f"(d[5]),"+f"(d[6]),"+f"(d[7]),"+f"(d[8]),"+f"(d[9]),"+f"(d[10]),"+f"(d[11]),"+f"(d[12]),"+f"(d[13]),"+f"(d[14]),"+f"(d[15]),"+f"(d[16]),"+f"(d[17]),"+f"(d[18]),"+f"(d[19]),"+f"(d[20]),"+f"(d[21]),"+f"(d[22]),"+f"(d[23])
      : "l"(da), "l"(db), "r"(sd));
}
template<> __device__ __forceinline__ void mma_ssp<56>(float* d, uint64_t da, uint64_t db, int sd) {
    asm volatile("{\n.reg .pred p;\nsetp.ne.b32 p, %30, 0;\nwgmma.mma_async.sync.aligned.m64n56k16.f32.bf16.bf16 {%0,%1,%2,%3,%4,%5,%6,%7,%8,%9,%10,%11,%12,%13,%14,%15,%16,%17,%18,%19,%20,%21,%22,%23,%24,%25,%26,%27}, %28, %29, p, 1, 1, 0, 1;\n}\n"
      : "+f"(d[0]),"+f"(d[1]),"+f"(d[2]),"+f"(d[3]),"+f"(d[4]),"+f"(d[5]),"+f"(d[6]),"+f"(d[7]),"+f"(d[8]),"+f"(d[9]),"+f"(d[10]),"+f"(d[11]),"+f"(d[12]),"+f"(d[13]),"+f"(d[14]),"+f"(d[15]),"+f"(d[16]),"+f"(d[17]),"+f"(d[18]),"+f"(d[19]),"+f"(d[20]),"+f"(d[21]),"+f"(d[22]),"+f"(d[23]),"+f"(d[24]),"+f"(d[25]),"+f"(d[26]),"+f"(d[27])
      : "l"(da), "l"(db), "r"(sd));
}
template<> __device__ __forceinline__ void mma_ssp<64>(float* d, uint64_t da, uint64_t db, int sd) {
    asm volatile("{\n.reg .pred p;\nsetp.ne.b32 p, %34, 0;\nwgmma.mma_async.sync.aligned.m64n64k16.f32.bf16.bf16 {%0,%1,%2,%3,%4,%5,%6,%7,%8,%9,%10,%11,%12,%13,%14,%15,%16,%17,%18,%19,%20,%21,%22,%23,%24,%25,%26,%27,%28,%29,%30,%31}, %32, %33, p, 1, 1, 0, 1;\n}\n"
      : "+f"(d[0]),"+f"(d[1]),"+f"(d[2]),"+f"(d[3]),"+f"(d[4]),"+f"(d[5]),"+f"(d[6]),"+f"(d[7]),"+f"(d[8]),"+f"(d[9]),"+f"(d[10]),"+f"(d[11]),"+f"(d[12]),"+f"(d[13]),"+f"(d[14]),"+f"(d[15]),"+f"(d[16]),"+f"(d[17]),"+f"(d[18]),"+f"(d[19]),"+f"(d[20]),"+f"(d[21]),"+f"(d[22]),"+f"(d[23]),"+f"(d[24]),"+f"(d[25]),"+f"(d[26]),"+f"(d[27]),"+f"(d[28]),"+f"(d[29]),"+f"(d[30]),"+f"(d[31])
      : "l"(da), "l"(db), "r"(sd));
}
template<> __device__ __forceinline__ void mma_ssp<80>(float* d, uint64_t da, uint64_t db, int sd) {
    asm volatile("{\n.reg .pred p;\nsetp.ne.b32 p, %42, 0;\nwgmma.mma_async.sync.aligned.m64n80k16.f32.bf16.bf16 {%0,%1,%2,%3,%4,%5,%6,%7,%8,%9,%10,%11,%12,%13,%14,%15,%16,%17,%18,%19,%20,%21,%22,%23,%24,%25,%26,%27,%28,%29,%30,%31,%32,%33,%34,%35,%36,%37,%38,%39}, %40, %41, p, 1, 1, 0, 1;\n}\n"
      : "+f"(d[0]),"+f"(d[1]),"+f"(d[2]),"+f"(d[3]),"+f"(d[4]),"+f"(d[5]),"+f"(d[6]),"+f"(d[7]),"+f"(d[8]),"+f"(d[9]),"+f"(d[10]),"+f"(d[11]),"+f"(d[12]),"+f"(d[13]),"+f"(d[14]),"+f"(d[15]),"+f"(d[16]),"+f"(d[17]),"+f"(d[18]),"+f"(d[19]),"+f"(d[20]),"+f"(d[21]),"+f"(d[22]),"+f"(d[23]),"+f"(d[24]),"+f"(d[25]),"+f"(d[26]),"+f"(d[27]),"+f"(d[28]),"+f"(d[29]),"+f"(d[30]),"+f"(d[31]),"+f"(d[32]),"+f"(d[33]),"+f"(d[34]),"+f"(d[35]),"+f"(d[36]),"+f"(d[37]),"+f"(d[38]),"+f"(d[39])
      : "l"(da), "l"(db), "r"(sd));
}
template<> __device__ __forceinline__ void mma_ssp<128>(float* d, uint64_t da, uint64_t db, int sd) {
    asm volatile("{\n.reg .pred p;\nsetp.ne.b32 p, %66, 0;\nwgmma.mma_async.sync.aligned.m64n128k16.f32.bf16.bf16 {%0,%1,%2,%3,%4,%5,%6,%7,%8,%9,%10,%11,%12,%13,%14,%15,%16,%17,%18,%19,%20,%21,%22,%23,%24,%25,%26,%27,%28,%29,%30,%31,%32,%33,%34,%35,%36,%37,%38,%39,%40,%41,%42,%43,%44,%45,%46,%47,%48,%49,%50,%51,%52,%53,%54,%55,%56,%57,%58,%59,%60,%61,%62,%63}, %64, %65, p, 1, 1, 0, 1;\n}\n"
      : "+f"(d[0]),"+f"(d[1]),"+f"(d[2]),"+f"(d[3]),"+f"(d[4]),"+f"(d[5]),"+f"(d[6]),"+f"(d[7]),"+f"(d[8]),"+f"(d[9]),"+f"(d[10]),"+f"(d[11]),"+f"(d[12]),"+f"(d[13]),"+f"(d[14]),"+f"(d[15]),"+f"(d[16]),"+f"(d[17]),"+f"(d[18]),"+f"(d[19]),"+f"(d[20]),"+f"(d[21]),"+f"(d[22]),"+f"(d[23]),"+f"(d[24]),"+f"(d[25]),"+f"(d[26]),"+f"(d[27]),"+f"(d[28]),"+f"(d[29]),"+f"(d[30]),"+f"(d[31]),"+f"(d[32]),"+f"(d[33]),"+f"(d[34]),"+f"(d[35]),"+f"(d[36]),"+f"(d[37]),"+f"(d[38]),"+f"(d[39]),"+f"(d[40]),"+f"(d[41]),"+f"(d[42]),"+f"(d[43]),"+f"(d[44]),"+f"(d[45]),"+f"(d[46]),"+f"(d[47]),"+f"(d[48]),"+f"(d[49]),"+f"(d[50]),"+f"(d[51]),"+f"(d[52]),"+f"(d[53]),"+f"(d[54]),"+f"(d[55]),"+f"(d[56]),"+f"(d[57]),"+f"(d[58]),"+f"(d[59]),"+f"(d[60]),"+f"(d[61]),"+f"(d[62]),"+f"(d[63])
      : "l"(da), "l"(db), "r"(sd));
}
template<> __device__ __forceinline__ void mma_ssp<152>(float* d, uint64_t da, uint64_t db, int sd) {
    asm volatile("{\n.reg .pred p;\nsetp.ne.b32 p, %78, 0;\nwgmma.mma_async.sync.aligned.m64n152k16.f32.bf16.bf16 {%0,%1,%2,%3,%4,%5,%6,%7,%8,%9,%10,%11,%12,%13,%14,%15,%16,%17,%18,%19,%20,%21,%22,%23,%24,%25,%26,%27,%28,%29,%30,%31,%32,%33,%34,%35,%36,%37,%38,%39,%40,%41,%42,%43,%44,%45,%46,%47,%48,%49,%50,%51,%52,%53,%54,%55,%56,%57,%58,%59,%60,%61,%62,%63,%64,%65,%66,%67,%68,%69,%70,%71,%72,%73,%74,%75}, %76, %77, p, 1, 1, 0, 1;\n}\n"
      : "+f"(d[0]),"+f"(d[1]),"+f"(d[2]),"+f"(d[3]),"+f"(d[4]),"+f"(d[5]),"+f"(d[6]),"+f"(d[7]),"+f"(d[8]),"+f"(d[9]),"+f"(d[10]),"+f"(d[11]),"+f"(d[12]),"+f"(d[13]),"+f"(d[14]),"+f"(d[15]),"+f"(d[16]),"+f"(d[17]),"+f"(d[18]),"+f"(d[19]),"+f"(d[20]),"+f"(d[21]),"+f"(d[22]),"+f"(d[23]),"+f"(d[24]),"+f"(d[25]),"+f"(d[26]),"+f"(d[27]),"+f"(d[28]),"+f"(d[29]),"+f"(d[30]),"+f"(d[31]),"+f"(d[32]),"+f"(d[33]),"+f"(d[34]),"+f"(d[35]),"+f"(d[36]),"+f"(d[37]),"+f"(d[38]),"+f"(d[39]),"+f"(d[40]),"+f"(d[41]),"+f"(d[42]),"+f"(d[43]),"+f"(d[44]),"+f"(d[45]),"+f"(d[46]),"+f"(d[47]),"+f"(d[48]),"+f"(d[49]),"+f"(d[50]),"+f"(d[51]),"+f"(d[52]),"+f"(d[53]),"+f"(d[54]),"+f"(d[55]),"+f"(d[56]),"+f"(d[57]),"+f"(d[58]),"+f"(d[59]),"+f"(d[60]),"+f"(d[61]),"+f"(d[62]),"+f"(d[63]),"+f"(d[64]),"+f"(d[65]),"+f"(d[66]),"+f"(d[67]),"+f"(d[68]),"+f"(d[69]),"+f"(d[70]),"+f"(d[71]),"+f"(d[72]),"+f"(d[73]),"+f"(d[74]),"+f"(d[75])
      : "l"(da), "l"(db), "r"(sd));
}
template<> __device__ __forceinline__ void mma_ssp<160>(float* d, uint64_t da, uint64_t db, int sd) {
    asm volatile("{\n.reg .pred p;\nsetp.ne.b32 p, %82, 0;\nwgmma.mma_async.sync.aligned.m64n160k16.f32.bf16.bf16 {%0,%1,%2,%3,%4,%5,%6,%7,%8,%9,%10,%11,%12,%13,%14,%15,%16,%17,%18,%19,%20,%21,%22,%23,%24,%25,%26,%27,%28,%29,%30,%31,%32,%33,%34,%35,%36,%37,%38,%39,%40,%41,%42,%43,%44,%45,%46,%47,%48,%49,%50,%51,%52,%53,%54,%55,%56,%57,%58,%59,%60,%61,%62,%63,%64,%65,%66,%67,%68,%69,%70,%71,%72,%73,%74,%75,%76,%77,%78,%79}, %80, %81, p, 1, 1, 0, 1;\n}\n"
      : "+f"(d[0]),"+f"(d[1]),"+f"(d[2]),"+f"(d[3]),"+f"(d[4]),"+f"(d[5]),"+f"(d[6]),"+f"(d[7]),"+f"(d[8]),"+f"(d[9]),"+f"(d[10]),"+f"(d[11]),"+f"(d[12]),"+f"(d[13]),"+f"(d[14]),"+f"(d[15]),"+f"(d[16]),"+f"(d[17]),"+f"(d[18]),"+f"(d[19]),"+f"(d[20]),"+f"(d[21]),"+f"(d[22]),"+f"(d[23]),"+f"(d[24]),"+f"(d[25]),"+f"(d[26]),"+f"(d[27]),"+f"(d[28]),"+f"(d[29]),"+f"(d[30]),"+f"(d[31]),"+f"(d[32]),"+f"(d[33]),"+f"(d[34]),"+f"(d[35]),"+f"(d[36]),"+f"(d[37]),"+f"(d[38]),"+f"(d[39]),"+f"(d[40]),"+f"(d[41]),"+f"(d[42]),"+f"(d[43]),"+f"(d[44]),"+f"(d[45]),"+f"(d[46]),"+f"(d[47]),"+f"(d[48]),"+f"(d[49]),"+f"(d[50]),"+f"(d[51]),"+f"(d[52]),"+f"(d[53]),"+f"(d[54]),"+f"(d[55]),"+f"(d[56]),"+f"(d[57]),"+f"(d[58]),"+f"(d[59]),"+f"(d[60]),"+f"(d[61]),"+f"(d[62]),"+f"(d[63]),"+f"(d[64]),"+f"(d[65]),"+f"(d[66]),"+f"(d[67]),"+f"(d[68]),"+f"(d[69]),"+f"(d[70]),"+f"(d[71]),"+f"(d[72]),"+f"(d[73]),"+f"(d[74]),"+f"(d[75]),"+f"(d[76]),"+f"(d[77]),"+f"(d[78]),"+f"(d[79])
      : "l"(da), "l"(db), "r"(sd));
}
template<> __device__ __forceinline__ void mma_ssp<168>(float* d, uint64_t da, uint64_t db, int sd) {
    asm volatile("{\n.reg .pred p;\nsetp.ne.b32 p, %86, 0;\nwgmma.mma_async.sync.aligned.m64n168k16.f32.bf16.bf16 {%0,%1,%2,%3,%4,%5,%6,%7,%8,%9,%10,%11,%12,%13,%14,%15,%16,%17,%18,%19,%20,%21,%22,%23,%24,%25,%26,%27,%28,%29,%30,%31,%32,%33,%34,%35,%36,%37,%38,%39,%40,%41,%42,%43,%44,%45,%46,%47,%48,%49,%50,%51,%52,%53,%54,%55,%56,%57,%58,%59,%60,%61,%62,%63,%64,%65,%66,%67,%68,%69,%70,%71,%72,%73,%74,%75,%76,%77,%78,%79,%80,%81,%82,%83}, %84, %85, p, 1, 1, 0, 1;\n}\n"
      : "+f"(d[0]),"+f"(d[1]),"+f"(d[2]),"+f"(d[3]),"+f"(d[4]),"+f"(d[5]),"+f"(d[6]),"+f"(d[7]),"+f"(d[8]),"+f"(d[9]),"+f"(d[10]),"+f"(d[11]),"+f"(d[12]),"+f"(d[13]),"+f"(d[14]),"+f"(d[15]),"+f"(d[16]),"+f"(d[17]),"+f"(d[18]),"+f"(d[19]),"+f"(d[20]),"+f"(d[21]),"+f"(d[22]),"+f"(d[23]),"+f"(d[24]),"+f"(d[25]),"+f"(d[26]),"+f"(d[27]),"+f"(d[28]),"+f"(d[29]),"+f"(d[30]),"+f"(d[31]),"+f"(d[32]),"+f"(d[33]),"+f"(d[34]),"+f"(d[35]),"+f"(d[36]),"+f"(d[37]),"+f"(d[38]),"+f"(d[39]),"+f"(d[40]),"+f"(d[41]),"+f"(d[42]),"+f"(d[43]),"+f"(d[44]),"+f"(d[45]),"+f"(d[46]),"+f"(d[47]),"+f"(d[48]),"+f"(d[49]),"+f"(d[50]),"+f"(d[51]),"+f"(d[52]),"+f"(d[53]),"+f"(d[54]),"+f"(d[55]),"+f"(d[56]),"+f"(d[57]),"+f"(d[58]),"+f"(d[59]),"+f"(d[60]),"+f"(d[61]),"+f"(d[62]),"+f"(d[63]),"+f"(d[64]),"+f"(d[65]),"+f"(d[66]),"+f"(d[67]),"+f"(d[68]),"+f"(d[69]),"+f"(d[70]),"+f"(d[71]),"+f"(d[72]),"+f"(d[73]),"+f"(d[74]),"+f"(d[75]),"+f"(d[76]),"+f"(d[77]),"+f"(d[78]),"+f"(d[79]),"+f"(d[80]),"+f"(d[81]),"+f"(d[82]),"+f"(d[83])
      : "l"(da), "l"(db), "r"(sd));
}
template<> __device__ __forceinline__ void mma_ssp<176>(float* d, uint64_t da, uint64_t db, int sd) {
    asm volatile("{\n.reg .pred p;\nsetp.ne.b32 p, %90, 0;\nwgmma.mma_async.sync.aligned.m64n176k16.f32.bf16.bf16 {%0,%1,%2,%3,%4,%5,%6,%7,%8,%9,%10,%11,%12,%13,%14,%15,%16,%17,%18,%19,%20,%21,%22,%23,%24,%25,%26,%27,%28,%29,%30,%31,%32,%33,%34,%35,%36,%37,%38,%39,%40,%41,%42,%43,%44,%45,%46,%47,%48,%49,%50,%51,%52,%53,%54,%55,%56,%57,%58,%59,%60,%61,%62,%63,%64,%65,%66,%67,%68,%69,%70,%71,%72,%73,%74,%75,%76,%77,%78,%79,%80,%81,%82,%83,%84,%85,%86,%87}, %88, %89, p, 1, 1, 0, 1;\n}\n"
      : "+f"(d[0]),"+f"(d[1]),"+f"(d[2]),"+f"(d[3]),"+f"(d[4]),"+f"(d[5]),"+f"(d[6]),"+f"(d[7]),"+f"(d[8]),"+f"(d[9]),"+f"(d[10]),"+f"(d[11]),"+f"(d[12]),"+f"(d[13]),"+f"(d[14]),"+f"(d[15]),"+f"(d[16]),"+f"(d[17]),"+f"(d[18]),"+f"(d[19]),"+f"(d[20]),"+f"(d[21]),"+f"(d[22]),"+f"(d[23]),"+f"(d[24]),"+f"(d[25]),"+f"(d[26]),"+f"(d[27]),"+f"(d[28]),"+f"(d[29]),"+f"(d[30]),"+f"(d[31]),"+f"(d[32]),"+f"(d[33]),"+f"(d[34]),"+f"(d[35]),"+f"(d[36]),"+f"(d[37]),"+f"(d[38]),"+f"(d[39]),"+f"(d[40]),"+f"(d[41]),"+f"(d[42]),"+f"(d[43]),"+f"(d[44]),"+f"(d[45]),"+f"(d[46]),"+f"(d[47]),"+f"(d[48]),"+f"(d[49]),"+f"(d[50]),"+f"(d[51]),"+f"(d[52]),"+f"(d[53]),"+f"(d[54]),"+f"(d[55]),"+f"(d[56]),"+f"(d[57]),"+f"(d[58]),"+f"(d[59]),"+f"(d[60]),"+f"(d[61]),"+f"(d[62]),"+f"(d[63]),"+f"(d[64]),"+f"(d[65]),"+f"(d[66]),"+f"(d[67]),"+f"(d[68]),"+f"(d[69]),"+f"(d[70]),"+f"(d[71]),"+f"(d[72]),"+f"(d[73]),"+f"(d[74]),"+f"(d[75]),"+f"(d[76]),"+f"(d[77]),"+f"(d[78]),"+f"(d[79]),"+f"(d[80]),"+f"(d[81]),"+f"(d[82]),"+f"(d[83]),"+f"(d[84]),"+f"(d[85]),"+f"(d[86]),"+f"(d[87])
      : "l"(da), "l"(db), "r"(sd));
}
template<> __device__ __forceinline__ void mma_ssp<184>(float* d, uint64_t da, uint64_t db, int sd) {
    asm volatile("{\n.reg .pred p;\nsetp.ne.b32 p, %94, 0;\nwgmma.mma_async.sync.aligned.m64n184k16.f32.bf16.bf16 {%0,%1,%2,%3,%4,%5,%6,%7,%8,%9,%10,%11,%12,%13,%14,%15,%16,%17,%18,%19,%20,%21,%22,%23,%24,%25,%26,%27,%28,%29,%30,%31,%32,%33,%34,%35,%36,%37,%38,%39,%40,%41,%42,%43,%44,%45,%46,%47,%48,%49,%50,%51,%52,%53,%54,%55,%56,%57,%58,%59,%60,%61,%62,%63,%64,%65,%66,%67,%68,%69,%70,%71,%72,%73,%74,%75,%76,%77,%78,%79,%80,%81,%82,%83,%84,%85,%86,%87,%88,%89,%90,%91}, %92, %93, p, 1, 1, 0, 1;\n}\n"
      : "+f"(d[0]),"+f"(d[1]),"+f"(d[2]),"+f"(d[3]),"+f"(d[4]),"+f"(d[5]),"+f"(d[6]),"+f"(d[7]),"+f"(d[8]),"+f"(d[9]),"+f"(d[10]),"+f"(d[11]),"+f"(d[12]),"+f"(d[13]),"+f"(d[14]),"+f"(d[15]),"+f"(d[16]),"+f"(d[17]),"+f"(d[18]),"+f"(d[19]),"+f"(d[20]),"+f"(d[21]),"+f"(d[22]),"+f"(d[23]),"+f"(d[24]),"+f"(d[25]),"+f"(d[26]),"+f"(d[27]),"+f"(d[28]),"+f"(d[29]),"+f"(d[30]),"+f"(d[31]),"+f"(d[32]),"+f"(d[33]),"+f"(d[34]),"+f"(d[35]),"+f"(d[36]),"+f"(d[37]),"+f"(d[38]),"+f"(d[39]),"+f"(d[40]),"+f"(d[41]),"+f"(d[42]),"+f"(d[43]),"+f"(d[44]),"+f"(d[45]),"+f"(d[46]),"+f"(d[47]),"+f"(d[48]),"+f"(d[49]),"+f"(d[50]),"+f"(d[51]),"+f"(d[52]),"+f"(d[53]),"+f"(d[54]),"+f"(d[55]),"+f"(d[56]),"+f"(d[57]),"+f"(d[58]),"+f"(d[59]),"+f"(d[60]),"+f"(d[61]),"+f"(d[62]),"+f"(d[63]),"+f"(d[64]),"+f"(d[65]),"+f"(d[66]),"+f"(d[67]),"+f"(d[68]),"+f"(d[69]),"+f"(d[70]),"+f"(d[71]),"+f"(d[72]),"+f"(d[73]),"+f"(d[74]),"+f"(d[75]),"+f"(d[76]),"+f"(d[77]),"+f"(d[78]),"+f"(d[79]),"+f"(d[80]),"+f"(d[81]),"+f"(d[82]),"+f"(d[83]),"+f"(d[84]),"+f"(d[85]),"+f"(d[86]),"+f"(d[87]),"+f"(d[88]),"+f"(d[89]),"+f"(d[90]),"+f"(d[91])
      : "l"(da), "l"(db), "r"(sd));
}
template<> __device__ __forceinline__ void mma_ssp<192>(float* d, uint64_t da, uint64_t db, int sd) {
    asm volatile("{\n.reg .pred p;\nsetp.ne.b32 p, %98, 0;\nwgmma.mma_async.sync.aligned.m64n192k16.f32.bf16.bf16 {%0,%1,%2,%3,%4,%5,%6,%7,%8,%9,%10,%11,%12,%13,%14,%15,%16,%17,%18,%19,%20,%21,%22,%23,%24,%25,%26,%27,%28,%29,%30,%31,%32,%33,%34,%35,%36,%37,%38,%39,%40,%41,%42,%43,%44,%45,%46,%47,%48,%49,%50,%51,%52,%53,%54,%55,%56,%57,%58,%59,%60,%61,%62,%63,%64,%65,%66,%67,%68,%69,%70,%71,%72,%73,%74,%75,%76,%77,%78,%79,%80,%81,%82,%83,%84,%85,%86,%87,%88,%89,%90,%91,%92,%93,%94,%95}, %96, %97, p, 1, 1, 0, 1;\n}\n"
      : "+f"(d[0]),"+f"(d[1]),"+f"(d[2]),"+f"(d[3]),"+f"(d[4]),"+f"(d[5]),"+f"(d[6]),"+f"(d[7]),"+f"(d[8]),"+f"(d[9]),"+f"(d[10]),"+f"(d[11]),"+f"(d[12]),"+f"(d[13]),"+f"(d[14]),"+f"(d[15]),"+f"(d[16]),"+f"(d[17]),"+f"(d[18]),"+f"(d[19]),"+f"(d[20]),"+f"(d[21]),"+f"(d[22]),"+f"(d[23]),"+f"(d[24]),"+f"(d[25]),"+f"(d[26]),"+f"(d[27]),"+f"(d[28]),"+f"(d[29]),"+f"(d[30]),"+f"(d[31]),"+f"(d[32]),"+f"(d[33]),"+f"(d[34]),"+f"(d[35]),"+f"(d[36]),"+f"(d[37]),"+f"(d[38]),"+f"(d[39]),"+f"(d[40]),"+f"(d[41]),"+f"(d[42]),"+f"(d[43]),"+f"(d[44]),"+f"(d[45]),"+f"(d[46]),"+f"(d[47]),"+f"(d[48]),"+f"(d[49]),"+f"(d[50]),"+f"(d[51]),"+f"(d[52]),"+f"(d[53]),"+f"(d[54]),"+f"(d[55]),"+f"(d[56]),"+f"(d[57]),"+f"(d[58]),"+f"(d[59]),"+f"(d[60]),"+f"(d[61]),"+f"(d[62]),"+f"(d[63]),"+f"(d[64]),"+f"(d[65]),"+f"(d[66]),"+f"(d[67]),"+f"(d[68]),"+f"(d[69]),"+f"(d[70]),"+f"(d[71]),"+f"(d[72]),"+f"(d[73]),"+f"(d[74]),"+f"(d[75]),"+f"(d[76]),"+f"(d[77]),"+f"(d[78]),"+f"(d[79]),"+f"(d[80]),"+f"(d[81]),"+f"(d[82]),"+f"(d[83]),"+f"(d[84]),"+f"(d[85]),"+f"(d[86]),"+f"(d[87]),"+f"(d[88]),"+f"(d[89]),"+f"(d[90]),"+f"(d[91]),"+f"(d[92]),"+f"(d[93]),"+f"(d[94]),"+f"(d[95])
      : "l"(da), "l"(db), "r"(sd));
}
template<> __device__ __forceinline__ void mma_ssp<200>(float* d, uint64_t da, uint64_t db, int sd) {
    asm volatile("{\n.reg .pred p;\nsetp.ne.b32 p, %102, 0;\nwgmma.mma_async.sync.aligned.m64n200k16.f32.bf16.bf16 {%0,%1,%2,%3,%4,%5,%6,%7,%8,%9,%10,%11,%12,%13,%14,%15,%16,%17,%18,%19,%20,%21,%22,%23,%24,%25,%26,%27,%28,%29,%30,%31,%32,%33,%34,%35,%36,%37,%38,%39,%40,%41,%42,%43,%44,%45,%46,%47,%48,%49,%50,%51,%52,%53,%54,%55,%56,%57,%58,%59,%60,%61,%62,%63,%64,%65,%66,%67,%68,%69,%70,%71,%72,%73,%74,%75,%76,%77,%78,%79,%80,%81,%82,%83,%84,%85,%86,%87,%88,%89,%90,%91,%92,%93,%94,%95,%96,%97,%98,%99}, %100, %101, p, 1, 1, 0, 1;\n}\n"
      : "+f"(d[0]),"+f"(d[1]),"+f"(d[2]),"+f"(d[3]),"+f"(d[4]),"+f"(d[5]),"+f"(d[6]),"+f"(d[7]),"+f"(d[8]),"+f"(d[9]),"+f"(d[10]),"+f"(d[11]),"+f"(d[12]),"+f"(d[13]),"+f"(d[14]),"+f"(d[15]),"+f"(d[16]),"+f"(d[17]),"+f"(d[18]),"+f"(d[19]),"+f"(d[20]),"+f"(d[21]),"+f"(d[22]),"+f"(d[23]),"+f"(d[24]),"+f"(d[25]),"+f"(d[26]),"+f"(d[27]),"+f"(d[28]),"+f"(d[29]),"+f"(d[30]),"+f"(d[31]),"+f"(d[32]),"+f"(d[33]),"+f"(d[34]),"+f"(d[35]),"+f"(d[36]),"+f"(d[37]),"+f"(d[38]),"+f"(d[39]),"+f"(d[40]),"+f"(d[41]),"+f"(d[42]),"+f"(d[43]),"+f"(d[44]),"+f"(d[45]),"+f"(d[46]),"+f"(d[47]),"+f"(d[48]),"+f"(d[49]),"+f"(d[50]),"+f"(d[51]),"+f"(d[52]),"+f"(d[53]),"+f"(d[54]),"+f"(d[55]),"+f"(d[56]),"+f"(d[57]),"+f"(d[58]),"+f"(d[59]),"+f"(d[60]),"+f"(d[61]),"+f"(d[62]),"+f"(d[63]),"+f"(d[64]),"+f"(d[65]),"+f"(d[66]),"+f"(d[67]),"+f"(d[68]),"+f"(d[69]),"+f"(d[70]),"+f"(d[71]),"+f"(d[72]),"+f"(d[73]),"+f"(d[74]),"+f"(d[75]),"+f"(d[76]),"+f"(d[77]),"+f"(d[78]),"+f"(d[79]),"+f"(d[80]),"+f"(d[81]),"+f"(d[82]),"+f"(d[83]),"+f"(d[84]),"+f"(d[85]),"+f"(d[86]),"+f"(d[87]),"+f"(d[88]),"+f"(d[89]),"+f"(d[90]),"+f"(d[91]),"+f"(d[92]),"+f"(d[93]),"+f"(d[94]),"+f"(d[95]),"+f"(d[96]),"+f"(d[97]),"+f"(d[98]),"+f"(d[99])
      : "l"(da), "l"(db), "r"(sd));
}
template<int SD> __device__ __forceinline__ void mma_n192_ss(float* d, uint64_t da, uint64_t db) {
    asm volatile("wgmma.mma_async.sync.aligned.m64n192k16.f32.bf16.bf16 {%0,%1,%2,%3,%4,%5,%6,%7,%8,%9,%10,%11,%12,%13,%14,%15,%16,%17,%18,%19,%20,%21,%22,%23,%24,%25,%26,%27,%28,%29,%30,%31,%32,%33,%34,%35,%36,%37,%38,%39,%40,%41,%42,%43,%44,%45,%46,%47,%48,%49,%50,%51,%52,%53,%54,%55,%56,%57,%58,%59,%60,%61,%62,%63,%64,%65,%66,%67,%68,%69,%70,%71,%72,%73,%74,%75,%76,%77,%78,%79,%80,%81,%82,%83,%84,%85,%86,%87,%88,%89,%90,%91,%92,%93,%94,%95}, %96, %97, %98, 1, 1, 0, 1;\n"
      : "+f"(d[0]),"+f"(d[1]),"+f"(d[2]),"+f"(d[3]),"+f"(d[4]),"+f"(d[5]),"+f"(d[6]),"+f"(d[7]),"+f"(d[8]),"+f"(d[9]),"+f"(d[10]),"+f"(d[11]),"+f"(d[12]),"+f"(d[13]),"+f"(d[14]),"+f"(d[15]),"+f"(d[16]),"+f"(d[17]),"+f"(d[18]),"+f"(d[19]),"+f"(d[20]),"+f"(d[21]),"+f"(d[22]),"+f"(d[23]),"+f"(d[24]),"+f"(d[25]),"+f"(d[26]),"+f"(d[27]),"+f"(d[28]),"+f"(d[29]),"+f"(d[30]),"+f"(d[31]),"+f"(d[32]),"+f"(d[33]),"+f"(d[34]),"+f"(d[35]),"+f"(d[36]),"+f"(d[37]),"+f"(d[38]),"+f"(d[39]),"+f"(d[40]),"+f"(d[41]),"+f"(d[42]),"+f"(d[43]),"+f"(d[44]),"+f"(d[45]),"+f"(d[46]),"+f"(d[47]),"+f"(d[48]),"+f"(d[49]),"+f"(d[50]),"+f"(d[51]),"+f"(d[52]),"+f"(d[53]),"+f"(d[54]),"+f"(d[55]),"+f"(d[56]),"+f"(d[57]),"+f"(d[58]),"+f"(d[59]),"+f"(d[60]),"+f"(d[61]),"+f"(d[62]),"+f"(d[63]),"+f"(d[64]),"+f"(d[65]),"+f"(d[66]),"+f"(d[67]),"+f"(d[68]),"+f"(d[69]),"+f"(d[70]),"+f"(d[71]),"+f"(d[72]),"+f"(d[73]),"+f"(d[74]),"+f"(d[75]),"+f"(d[76]),"+f"(d[77]),"+f"(d[78]),"+f"(d[79]),"+f"(d[80]),"+f"(d[81]),"+f"(d[82]),"+f"(d[83]),"+f"(d[84]),"+f"(d[85]),"+f"(d[86]),"+f"(d[87]),"+f"(d[88]),"+f"(d[89]),"+f"(d[90]),"+f"(d[91]),"+f"(d[92]),"+f"(d[93]),"+f"(d[94]),"+f"(d[95])
      : "l"(da), "l"(db), "n"(SD));
}
template<int SD> __device__ __forceinline__ void mma_n64_ss(float* d, uint64_t da, uint64_t db) {
    asm volatile("wgmma.mma_async.sync.aligned.m64n64k16.f32.bf16.bf16 {%0,%1,%2,%3,%4,%5,%6,%7,%8,%9,%10,%11,%12,%13,%14,%15,%16,%17,%18,%19,%20,%21,%22,%23,%24,%25,%26,%27,%28,%29,%30,%31}, %32, %33, %34, 1, 1, 0, 1;\n"
      : "+f"(d[0]),"+f"(d[1]),"+f"(d[2]),"+f"(d[3]),"+f"(d[4]),"+f"(d[5]),"+f"(d[6]),"+f"(d[7]),"+f"(d[8]),"+f"(d[9]),"+f"(d[10]),"+f"(d[11]),"+f"(d[12]),"+f"(d[13]),"+f"(d[14]),"+f"(d[15]),"+f"(d[16]),"+f"(d[17]),"+f"(d[18]),"+f"(d[19]),"+f"(d[20]),"+f"(d[21]),"+f"(d[22]),"+f"(d[23]),"+f"(d[24]),"+f"(d[25]),"+f"(d[26]),"+f"(d[27]),"+f"(d[28]),"+f"(d[29]),"+f"(d[30]),"+f"(d[31])
      : "l"(da), "l"(db), "n"(SD));
}
template<int SD> __device__ __forceinline__ void mma_n128_ss(float* d, uint64_t da, uint64_t db) {
    asm volatile("wgmma.mma_async.sync.aligned.m64n128k16.f32.bf16.bf16 {%0,%1,%2,%3,%4,%5,%6,%7,%8,%9,%10,%11,%12,%13,%14,%15,%16,%17,%18,%19,%20,%21,%22,%23,%24,%25,%26,%27,%28,%29,%30,%31,%32,%33,%34,%35,%36,%37,%38,%39,%40,%41,%42,%43,%44,%45,%46,%47,%48,%49,%50,%51,%52,%53,%54,%55,%56,%57,%58,%59,%60,%61,%62,%63}, %64, %65, %66, 1, 1, 0, 1;\n"
      : "+f"(d[0]),"+f"(d[1]),"+f"(d[2]),"+f"(d[3]),"+f"(d[4]),"+f"(d[5]),"+f"(d[6]),"+f"(d[7]),"+f"(d[8]),"+f"(d[9]),"+f"(d[10]),"+f"(d[11]),"+f"(d[12]),"+f"(d[13]),"+f"(d[14]),"+f"(d[15]),"+f"(d[16]),"+f"(d[17]),"+f"(d[18]),"+f"(d[19]),"+f"(d[20]),"+f"(d[21]),"+f"(d[22]),"+f"(d[23]),"+f"(d[24]),"+f"(d[25]),"+f"(d[26]),"+f"(d[27]),"+f"(d[28]),"+f"(d[29]),"+f"(d[30]),"+f"(d[31]),"+f"(d[32]),"+f"(d[33]),"+f"(d[34]),"+f"(d[35]),"+f"(d[36]),"+f"(d[37]),"+f"(d[38]),"+f"(d[39]),"+f"(d[40]),"+f"(d[41]),"+f"(d[42]),"+f"(d[43]),"+f"(d[44]),"+f"(d[45]),"+f"(d[46]),"+f"(d[47]),"+f"(d[48]),"+f"(d[49]),"+f"(d[50]),"+f"(d[51]),"+f"(d[52]),"+f"(d[53]),"+f"(d[54]),"+f"(d[55]),"+f"(d[56]),"+f"(d[57]),"+f"(d[58]),"+f"(d[59]),"+f"(d[60]),"+f"(d[61]),"+f"(d[62]),"+f"(d[63])
      : "l"(da), "l"(db), "n"(SD));
}
template<int SD> __device__ __forceinline__ void mma_n64_rs(float* d, uint32_t a0, uint32_t a1, uint32_t a2, uint32_t a3, uint64_t db) {
    asm volatile("wgmma.mma_async.sync.aligned.m64n64k16.f32.bf16.bf16 {%0,%1,%2,%3,%4,%5,%6,%7,%8,%9,%10,%11,%12,%13,%14,%15,%16,%17,%18,%19,%20,%21,%22,%23,%24,%25,%26,%27,%28,%29,%30,%31}, {%32,%33,%34,%35}, %36, %37, 1, 1, 0;\n"
      : "+f"(d[0]),"+f"(d[1]),"+f"(d[2]),"+f"(d[3]),"+f"(d[4]),"+f"(d[5]),"+f"(d[6]),"+f"(d[7]),"+f"(d[8]),"+f"(d[9]),"+f"(d[10]),"+f"(d[11]),"+f"(d[12]),"+f"(d[13]),"+f"(d[14]),"+f"(d[15]),"+f"(d[16]),"+f"(d[17]),"+f"(d[18]),"+f"(d[19]),"+f"(d[20]),"+f"(d[21]),"+f"(d[22]),"+f"(d[23]),"+f"(d[24]),"+f"(d[25]),"+f"(d[26]),"+f"(d[27]),"+f"(d[28]),"+f"(d[29]),"+f"(d[30]),"+f"(d[31])
      : "r"(a0), "r"(a1), "r"(a2), "r"(a3), "l"(db), "n"(SD));
}
template<int SD> __device__ __forceinline__ void mma_n64_sk(float* d, uint64_t da, uint64_t db) {
    asm volatile("wgmma.mma_async.sync.aligned.m64n64k16.f32.bf16.bf16 {%0,%1,%2,%3,%4,%5,%6,%7,%8,%9,%10,%11,%12,%13,%14,%15,%16,%17,%18,%19,%20,%21,%22,%23,%24,%25,%26,%27,%28,%29,%30,%31}, %32, %33, %34, 1, 1, 0, 0;\n"
      : "+f"(d[0]),"+f"(d[1]),"+f"(d[2]),"+f"(d[3]),"+f"(d[4]),"+f"(d[5]),"+f"(d[6]),"+f"(d[7]),"+f"(d[8]),"+f"(d[9]),"+f"(d[10]),"+f"(d[11]),"+f"(d[12]),"+f"(d[13]),"+f"(d[14]),"+f"(d[15]),"+f"(d[16]),"+f"(d[17]),"+f"(d[18]),"+f"(d[19]),"+f"(d[20]),"+f"(d[21]),"+f"(d[22]),"+f"(d[23]),"+f"(d[24]),"+f"(d[25]),"+f"(d[26]),"+f"(d[27]),"+f"(d[28]),"+f"(d[29]),"+f"(d[30]),"+f"(d[31])
      : "l"(da), "l"(db), "n"(SD));
}
template<int SD> __device__ __forceinline__ void mma_n24_rs(float* d, uint32_t a0, uint32_t a1, uint32_t a2, uint32_t a3, uint64_t db) {
    asm volatile("wgmma.mma_async.sync.aligned.m64n24k16.f32.bf16.bf16 {%0,%1,%2,%3,%4,%5,%6,%7,%8,%9,%10,%11}, {%12,%13,%14,%15}, %16, %17, 1, 1, 1;\n"
      : "+f"(d[0]),"+f"(d[1]),"+f"(d[2]),"+f"(d[3]),"+f"(d[4]),"+f"(d[5]),"+f"(d[6]),"+f"(d[7]),"+f"(d[8]),"+f"(d[9]),"+f"(d[10]),"+f"(d[11])
      : "r"(a0), "r"(a1), "r"(a2), "r"(a3), "l"(db), "n"(SD));
}

__host__ __device__ constexpr uint64_t mkdesc(uint32_t addr, uint32_t lbo, uint32_t sbo, uint32_t swz) {
    return (uint64_t)((addr & 0x3FFFF) >> 4) | ((uint64_t)(lbo >> 4) << 16) | ((uint64_t)(sbo >> 4) << 32) | ((uint64_t)swz << 62);
}
#define WG_FENCE() asm volatile("wgmma.fence.sync.aligned;" ::: "memory")
#define WG_COMMIT() asm volatile("wgmma.commit_group.sync.aligned;" ::: "memory")
#define WG_WAIT(n) asm volatile("wgmma.wait_group.sync.aligned " #n ";" ::: "memory")
template<int N> __device__ __forceinline__ void keep(float* r) {
#pragma unroll
    for (int i = 0; i < N; i++) asm volatile("" : "+f"(r[i]) :: "memory");
}
template<int N> __device__ __forceinline__ void kill(float* r) {
#pragma unroll
    for (int i = 0; i < N; i++) asm volatile("" : "=f"(r[i]));
}
template<int N> __device__ __forceinline__ void keep(uint32_t* r) {
#pragma unroll
    for (int i = 0; i < N; i++) asm volatile("" : "+r"(r[i]) :: "memory");
}
__device__ __forceinline__ uint32_t cl(uint32_t a) { return a + ((blockIdx.x & 1) << 24); }
__device__ __forceinline__ void mbar_init(uint32_t a, uint32_t c) { asm volatile("mbarrier.init.shared::cta.b64 [%0], %1;" :: "r"(cl(a)), "r"(c) : "memory"); }
__device__ __forceinline__ void mbar_arrive(uint32_t a) { asm volatile("mbarrier.arrive.shared::cta.b64 _, [%0];" :: "r"(cl(a)) : "memory"); }
__device__ __forceinline__ void mbar_wait(uint32_t a, uint32_t ph) {
    asm volatile("{\n.reg .pred p, q;\n.reg .u32 n;\nmov.u32 n, 0;\n"
        "LW:\nmbarrier.try_wait.parity.shared::cta.b64 p, [%0], %1;\n@p bra LD;\n"
        "add.u32 n, n, 1;\nsetp.gt.u32 q, n, 2000000;\n@q trap;\nbra LW;\nLD:\n}" :: "r"(cl(a)), "r"(ph) : "memory");
}
__device__ __forceinline__ void mbar_wait_raw(uint32_t addr, uint32_t ph) {
    asm volatile("{\n.reg .pred p, q;\n.reg .u32 n;\nmbarrier.try_wait.parity.shared::cta.b64 p, [%0], %1;\n@p bra LD;\nmov.u32 n, 0;\n"
        "LW:\nmbarrier.try_wait.parity.shared::cta.b64 p, [%0], %1;\n@p bra LD;\n"
        "add.u32 n, n, 1;\nsetp.gt.u32 q, n, 2000000;\n@q trap;\nbra LW;\nLD:\n}" :: "r"(addr), "r"(ph) : "memory");
}
__device__ __forceinline__ void flag_wait(const unsigned* p, unsigned target) {
    asm volatile("{\n.reg .pred p, q;\n.reg .u32 n, v;\nmov.u32 n, 0;\n"
        "LW:\nld.acquire.gpu.global.u32 v, [%0];\nsub.u32 v, v, %1;\nsetp.ge.s32 p, v, 0;\n@p bra LD;\n"
        "nanosleep.u32 100;\nadd.u32 n, n, 1;\nsetp.gt.u32 q, n, 4000000;\n@q trap;\nbra LW;\nLD:\n}" :: "l"(p), "r"(target) : "memory");
}
__device__ __forceinline__ void red_release(unsigned* p, unsigned v) { asm volatile("red.release.gpu.global.add.u32 [%0], %1;" :: "l"(p), "r"(v) : "memory"); }
__device__ __forceinline__ void red_relaxed(unsigned* p, unsigned v) { asm volatile("red.relaxed.gpu.global.add.u32 [%0], %1;" :: "l"(p), "r"(v) : "memory"); }
__device__ __forceinline__ void st_release(unsigned* p, unsigned v) { asm volatile("st.release.gpu.global.u32 [%0], %1;" :: "l"(p), "r"(v) : "memory"); }
__device__ __forceinline__ unsigned ld_relaxed(const unsigned* p) { unsigned v; asm volatile("ld.relaxed.gpu.global.u32 %0, [%1];" : "=r"(v) : "l"(p) : "memory"); return v; }
__device__ __forceinline__ unsigned ld_acquire(const unsigned* p) { unsigned v; asm volatile("ld.acquire.gpu.global.u32 %0, [%1];" : "=r"(v) : "l"(p) : "memory"); return v; }
__device__ __forceinline__ unsigned get_tag() { return ld_relaxed(&g_done) / (4 * NCTA) + 1; }
__device__ __forceinline__ unsigned long long ld_tagged(const unsigned long long* p) {
    unsigned long long v; asm volatile("ld.relaxed.gpu.global.b64 %0, [%1];" : "=l"(v) : "l"(p) : "memory"); return v;
}
__device__ __forceinline__ void fence_async() { asm volatile("fence.proxy.async;" ::: "memory"); }
__device__ __forceinline__ void bar_sync(int id, int n) { asm volatile("bar.sync %0, %1;" :: "r"(id), "r"(n) : "memory"); }
__device__ __forceinline__ void bar_arrive(int id, int n) { asm volatile("bar.arrive %0, %1;" :: "r"(id), "r"(n) : "memory"); }
#define ELECT_BEGIN "{\n.reg .pred p, e;\nelect.sync _|p, 0xffffffff;\nsetp.ne.and.u32 e, %1, 0, p;\n@e mbarrier.arrive.expect_tx.shared::cta.b64 _, [%0], %1;\n"
__device__ __forceinline__ void bulk_load(uint32_t dst, const void* src, uint32_t bytes, uint32_t bar, uint32_t tx) {
    asm volatile(ELECT_BEGIN "@p cp.async.bulk.shared::cluster.global.mbarrier::complete_tx::bytes [%2], [%3], %4, [%0];\n}"
        :: "r"(cl(bar)), "r"(tx), "r"(cl(dst)), "l"(src), "r"(bytes) : "memory");
}
__device__ __forceinline__ void send_half(int kb) {
    const uint32_t off = A_OFF + (blockIdx.x & 1) * 8192 + kb * 16384, peer = ((blockIdx.x & 1) ^ 1) << 24;
    asm volatile(ELECT_BEGIN "@p cp.async.bulk.shared::cluster.shared::cta.mbarrier::complete_tx::bytes [%2], [%3], 8192, [%4];\n}"
        :: "r"(cl(BAR_FULLA + 8 * kb)), "r"(8192), "r"(off + peer), "r"(cl(off)), "r"(BAR_FULLA + 8 * kb + peer) : "memory");
}
__device__ __forceinline__ void tma2d(uint32_t dst, const CUtensorMap* m, int c0, int c1, uint32_t bar, uint32_t tx) {
    asm volatile(ELECT_BEGIN "@p cp.async.bulk.tensor.2d.shared::cluster.global.mbarrier::complete_tx::bytes [%2], [%3, {%4, %5}], [%0];\n}"
        :: "r"(cl(bar)), "r"(tx), "r"(cl(dst)), "l"(m), "r"(c0), "r"(c1) : "memory");
}
__device__ __forceinline__ void tma3d(uint32_t dst, const CUtensorMap* m, int c1, int c2, uint32_t bar, uint32_t tx) {
    asm volatile(ELECT_BEGIN "@p cp.async.bulk.tensor.3d.shared::cluster.global.mbarrier::complete_tx::bytes [%2], [%3, {%6, %4, %5}], [%0];\n}"
        :: "r"(cl(bar)), "r"(tx), "r"(cl(dst)), "l"(m), "r"(c1), "r"(c2), "r"(0) : "memory");
}
__device__ __forceinline__ void tma4d(uint32_t dst, const CUtensorMap* m, int c1, int c2, int c3, uint32_t bar, uint32_t tx) {
    asm volatile(ELECT_BEGIN "@p cp.async.bulk.tensor.4d.shared::cluster.global.mbarrier::complete_tx::bytes [%2], [%3, {%7, %4, %5, %6}], [%0];\n}"
        :: "r"(cl(bar)), "r"(tx), "r"(cl(dst)), "l"(m), "r"(c1), "r"(c2), "r"(c3), "r"(0) : "memory");
}
__device__ __forceinline__ void tma5d(uint32_t dst, const CUtensorMap* m, int c3, int c4, uint32_t bar, uint32_t tx) {
    asm volatile(ELECT_BEGIN "@p cp.async.bulk.tensor.5d.shared::cluster.global.mbarrier::complete_tx::bytes [%2], [%3, {%6, %6, %6, %4, %5}], [%0];\n}"
        :: "r"(cl(bar)), "r"(tx), "r"(cl(dst)), "l"(m), "r"(c3), "r"(c4), "r"(0) : "memory");
}
__device__ __forceinline__ uint32_t pack_bf16(float lo, float hi) {
    uint32_t r; asm("cvt.rn.bf16x2.f32 %0, %1, %2;" : "=r"(r) : "f"(hi), "f"(lo)); return r;
}
__device__ __forceinline__ uint32_t half_bf16(float lo, float hi) {
    uint32_t r; asm("mul.rn.bf16x2 %0, %1, %2;" : "=r"(r) : "r"(pack_bf16(lo, hi)), "r"(0x3f003f00u)); return r;
}
__device__ __forceinline__ float bf_lo(uint32_t v) { return __uint_as_float(v << 16); }
__device__ __forceinline__ float bf_hi(uint32_t v) { return __uint_as_float(v & 0xffff0000u); }
__device__ __forceinline__ float2 lds64(uint32_t a) { float2 v; asm volatile("ld.shared.v2.f32 {%0,%1}, [%2];" : "=f"(v.x), "=f"(v.y) : "r"(cl(a))); return v; }
__device__ __forceinline__ uint32_t lds32(uint32_t a) { uint32_t v; asm volatile("ld.shared.u32 %0, [%1];" : "=r"(v) : "r"(cl(a)) : "memory"); return v; }
__device__ __forceinline__ void l2_prefetch(const void* p, uint32_t bytes, uint32_t pause) {
#pragma unroll 1
    for (uint32_t o = (threadIdx.x & 31) * 128; o < bytes; o += 4096) {
        asm volatile("prefetch.global.L2 [%0];" :: "l"((const uint8_t*)p + o) : "memory");
        if (pause) asm volatile("nanosleep.u32 %0;" :: "r"(pause));
    }
    __syncwarp();
}
__device__ __forceinline__ void l2_prefetch_bulk(const void* p, uint32_t bytes) {
    asm volatile("{\n.reg .pred p;\nelect.sync _|p, 0xffffffff;\n@p cp.async.bulk.prefetch.L2.global [%0], %1;\n}" :: "l"(p), "r"(bytes) : "memory");
}
__device__ __forceinline__ float ex2(float x) { float y; asm("ex2.approx.ftz.f32 %0, %1;" : "=f"(y) : "f"(x)); return y; }

__device__ __forceinline__ int cta_m() { return blockIdx.x >> 3; }
__device__ __forceinline__ int cta_j() { return blockIdx.x & 7; }
__device__ __forceinline__ bool cta_isG() { return blockIdx.x < 128 && (blockIdx.x & 7) < 3; }
#define AORDER 0x43021000
__device__ __forceinline__ int cta_aidx() {
    const int j = blockIdx.x & 7;
    return blockIdx.x >= 128 ? blockIdx.x - 128 : 4 + ((AORDER >> (4 * j)) & 7) * 16 + (blockIdx.x >> 3);
}

#define MINIW 0x01122000
__device__ __forceinline__ int mini_w() { return (MINIW >> (4 * cta_j())) & 3; }
__device__ __forceinline__ int has_mini() { return mini_w() != 0; }
__device__ __forceinline__ int num_jobs() { return has_mini() + (cta_isG() ? 4 : 2); }
__device__ __forceinline__ int job_id(int q) {
    const int w = q - has_mini(), j = cta_j();
    const uint32_t below = MINIW & ((1u << (4 * j)) - 1);
    return w < 0 ? __popc(below & 0x11111111u) + 2 * __popc(below & 0x22222222u) : 6 + (w < 2 ? 8 * w + j : 10 + 3 * w + j);
}
__device__ __forceinline__ int job_chunk(int id) { return id < 6 ? id : 3 * id - 12; }
__device__ __forceinline__ int job_bar(int q) { return q < 3 ? 11 + q : (q == 3 ? 15 : 3); }

template<int J>
__device__ __forceinline__ void qkv_mainloop(uint32_t* v, int wg, bool elect) {
    constexpr int O = (216 * J) % 64, N1 = 64 - O, N2 = 152 + O, NCH = (O + 216 + 63) / 64, NST = NCH == 4 ? 9 : 7;
    constexpr uint64_t dB = mkdesc(B_OFF, 2048, 1024, 1);
    const uint64_t dA = mkdesc(A_OFF, 16, 1024, 1) + (uint64_t)((wg - 1) * (8192 >> 4));
    int st = NST == 7 ? 6 : 0; uint32_t ph = 0;
    float acc[108];
#pragma unroll 1
    for (int ks = 0; ks < 36; ks += 2) {
        int st1 = st + 1; uint32_t ph1 = ph; if (st1 == NST) { st1 = 0; ph1 ^= 1; }
        if ((ks & 3) == 0 && ((wg ^ blockIdx.x) & 1) == 0) mbar_wait(BAR_FULLA + 2 * ks, 0);
        mbar_wait(BAR_FULLW + 8 * st, ph);
        mbar_wait(BAR_FULLW + 8 * st1, ph1);
        const uint64_t a = dA + (uint64_t)((ks >> 2) * (16384 >> 4) + (ks & 3) * 2);
        WG_FENCE();
#pragma unroll
        for (int k = 0; k < 2; k++) {
            const uint64_t b = dB + (uint64_t)((k ? st1 : st) * (NCH * 2048 >> 4));
            if (N2 <= 200) mma_ssp<(N2 <= 200 ? N2 : 128)>(acc + N1 / 2, a + 2 * k, b + (2048 >> 4), ks + k);
            else { mma_ssp<128>(acc + N1 / 2, a + 2 * k, b + (2048 >> 4), ks + k); mma_ssp<80>(acc + N1 / 2 + 64, a + 2 * k, b + (6144 >> 4), ks + k); }
            mma_ssp<N1>(acc, a + 2 * k, b + (2 * O >> 4), ks + k);
        }
        WG_COMMIT();
        WG_WAIT(1);
        if ((threadIdx.x & 127) < 2 && ks > 0) {
            int sp = st - 1 - (threadIdx.x & 1); if (sp < 0) sp += NST;
            mbar_arrive(BAR_EMPTYW + 8 * sp);
        }
        st = st1 + 1; ph = ph1; if (st == NST) { st = 0; ph ^= 1; }
    }
    WG_WAIT(0);
    keep<108>(acc);
    if ((threadIdx.x & 127) < 3) mbar_arrive((threadIdx.x & 127) == 2 ? BAR_WDONE : BAR_EMPTYW + 8 * (NST - 1 - (threadIdx.x & 1)));
    if (wg == 1) TS(16);
    constexpr float QS = 0.23570226f * 1.44269504f;
#pragma unroll
    for (int i = 0; i < 54; i++) v[i] = 216 * J + 8 * (i >> 1) < DM ? pack_bf16(acc[2 * i] * QS, acc[2 * i + 1] * QS) : pack_bf16(acc[2 * i], acc[2 * i + 1]);
}

__device__ __forceinline__ uint64_t sel_desc(int q) { return mkdesc(ONE_OFF, 0, 0, 0) + (uint64_t)(q * (128 >> 4)) + ((uint64_t)((6 - q) * (128 >> 4)) << 16); }
constexpr uint64_t SEL2 = (uint64_t)(128 >> 4) << 16;
constexpr uint64_t BIAS_DESC = mkdesc(BIAS_OFF, 1024, 0, 1);
template<int W>
__device__ __forceinline__ void mini_mainloop(float* acc0, float* acc1, bool elect) {
    constexpr uint64_t dA = mkdesc(A_OFF, 16, 1024, 1), dB = mkdesc(B_OFF, 6144, 1024, 1);
    WG_FENCE();
    if (W == 1) { mma_n64_ss<0>(acc0, sel_desc(0), BIAS_DESC); mma_n64_ss<0>(acc1, sel_desc(0) + SEL2, BIAS_DESC); }
    else { mma_n128_ss<0>(acc0, sel_desc(0), BIAS_DESC); mma_n128_ss<0>(acc1, sel_desc(0) + SEL2, BIAS_DESC); }
    WG_COMMIT();
    int st = 0;
#pragma unroll 1
    for (int s = 0; s < 6 * W; s++) {
        mbar_wait(BAR_FULLB + 8 * st, s >= 6);
        if (s == 6 * W - 1) bar_arrive(9, 256);
        WG_FENCE();
#pragma unroll
        for (int k = 0; k < 6 / W; k++) {
            const int ks = (6 / W) * s + k;
            const uint64_t a = dA + (uint64_t)((ks >> 2) * (16384 >> 4) + (ks & 3) * 2), b = dB + (uint64_t)(st * (12288 >> 4) + k * (2048 >> 4));
            if (W == 1) { mma_n64_ss<1>(acc0, a, b); mma_n64_ss<1>(acc1, a + (8192 >> 4), b); }
            else { mma_n128_ss<1>(acc0, a, b); mma_n128_ss<1>(acc1, a + (8192 >> 4), b); }
        }
        WG_COMMIT();
        WG_WAIT(1);
        if (elect && s > 0) mbar_arrive(BAR_EMPTYB + 8 * (st == 0 ? 5 : st - 1));
        if (++st == 6) st = 0;
    }
    WG_WAIT(0);
    if (elect) mbar_arrive(BAR_EMPTYB + 8 * 5);
    keep<32 * W>(acc0); keep<32 * W>(acc1);
}
__device__ __forceinline__ void job_mainloop(float* acc0, float* acc1, int q, bool g2, uint32_t xa, bool elect) {
    constexpr uint64_t dB = mkdesc(B_OFF, 4096, 1024, 1);
    const bool last = q == num_jobs() - 1, releaseA = g2 || last, handoff = !g2 && (!last || cta_isG());
    WG_FENCE();
    mma_n192_ss<0>(acc0, sel_desc(g2 ? 5 : q), BIAS_DESC); mma_n192_ss<0>(acc1, sel_desc(g2 ? 5 : q) + SEL2, BIAS_DESC);
    WG_COMMIT();
    if (q > 0) bar_sync(8 + (q & 1), 256);
    const int nturn = g2 ? 27 : 3;
    int grp = 0; uint32_t pa = 1;
#pragma unroll 1
    for (int u = 0; u < nturn; u++) {
        const uint32_t par = (q + u + (mini_w() >> 1)) & 1;
        if (g2 && (u == 3 || u == 12 || u == 24)) TS2(u == 3 ? 4 : (u == 12 ? 5 : 6));
        if (u == 24) {
            mbar_wait(BAR_FULLA, pa); mbar_wait(BAR_FULLA + 8, pa); mbar_wait(BAR_FULLA + 16, pa);
            WG_WAIT(0);
            keep<96>(acc0); keep<96>(acc1);
            if (elect) { mbar_arrive(BAR_EMPTYB + 8 * 5); mbar_arrive(BAR_EMPTYA + 8 * 8); }
#pragma unroll
            for (int i2 = 0; i2 < 12; i2++) {
#pragma unroll
                for (int mh = 0; mh < 2; mh++) {
                    float* a = (mh ? acc1 : acc0) + 8 * i2;
                    uint32_t r[4];
                    asm volatile("ldmatrix.sync.aligned.m8n8.x4.shared.b16 {%0,%1,%2,%3}, [%4];" : "=r"(r[0]), "=r"(r[1]), "=r"(r[2]), "=r"(r[3])
                        : "r"(cl((xa ^ ((i2 & 3) << 5)) + (i2 >> 2) * 16384 + mh * 8192)) : "memory");
#pragma unroll
                    for (int e = 0; e < 4; e++) { a[2 * e] = fmaf(bf_lo(r[e]), 2.0f, a[2 * e]); a[2 * e + 1] = fmaf(bf_hi(r[e]), 2.0f, a[2 * e + 1]); }
                }
            }
            keep<96>(acc0); keep<96>(acc1);
            grp = 1;
        }
        const uint64_t dAu = (!g2 ? mkdesc(A_OFF, 16, 1024, 1) : (u < 24 ? mkdesc(A_OFF, 16, 512, 2) : mkdesc(A_OFF, 128, 1024, 0))) + (uint64_t)(grp * (3 * 16384 >> 4));
        const uint32_t kst = u >= 24 ? (256 >> 4) : (32 >> 4), hst = !g2 ? (64 >> 4) : (u < 24 ? (8192 >> 4) : (512 >> 4)), mst = (g2 && u < 24) ? (4096 >> 4) : (8192 >> 4);
#pragma unroll
        for (int st = 0; st < 6; st++) {
            const int kb = st >> 1, half = st & 1;
            if (half == 0 && g2) mbar_wait(BAR_FULLA + 8 * (3 * grp + kb), pa);
            mbar_wait(BAR_FULLB + 8 * st, par);
            if (st == 5 && u == 2 && handoff) bar_arrive(8 + ((q + 1) & 1), 256);
            WG_FENCE();
#pragma unroll
            for (int k = 0; k < 2; k++) {
                const uint64_t a = dAu + (uint64_t)(kb * (16384 >> 4) + half * hst + k * kst);
                const uint64_t b = dB + (uint64_t)((st * 12288 + k * 2048) >> 4);
                mma_n192_ss<1>(acc0, a, b); mma_n192_ss<1>(acc1, a + mst, b);
            }
            WG_COMMIT();
            WG_WAIT(1);
            if (elect && (st > 0 || u > 0)) {
                if (st > 0 || u != 24) {
                    mbar_arrive(BAR_EMPTYB + 8 * ((st + 5) % 6));
                    if (half == 0 && releaseA) mbar_arrive(BAR_EMPTYA + 8 * (kb == 0 && grp == 0 ? 8 : 3 * grp + kb - 1));
                }
                if (st == 1 && u == 24) { mbar_arrive(BAR_EMPTYA); mbar_arrive(BAR_EMPTYA + 8); mbar_arrive(BAR_EMPTYA + 16); }
            }
        }
        if (++grp == 3) { grp = 0; pa ^= 1; }
    }
    WG_WAIT(0);
    if (elect && !g2) { mbar_arrive(BAR_EMPTYB + 8 * 5); if (releaseA) mbar_arrive(BAR_EMPTYA + 8 * 8); }
    keep<96>(acc0); keep<96>(acc1);
}

__device__ __forceinline__ void epilogue_gelu(const float* acc, uint8_t* hp, int nchunk) {
#pragma unroll
    for (int i4 = 0; i4 < 6; i4++) {
        if ((i4 == 2 || i4 == 4) && i4 == 2 * nchunk) break;
        float z[16];
#define XX(e) acc[4 * (8 * (i4 >> 1) + (i4 & 1) + 2 * ((e) >> 2)) + ((e) & 3)]
#pragma unroll
        for (int e = 0; e < 16; e++) z[e] = XX(e) * fmaf(XX(e) * XX(e), 0.035677408f, 0.79788456f);
#pragma unroll
        for (int e = 0; e < 16; e++) asm("tanh.approx.f32 %0, %0;" : "+f"(z[e]));
#pragma unroll
        for (int e = 0; e < 16; e++) z[e] = fmaf(XX(e), z[e], XX(e));
#undef XX
#pragma unroll
        for (int r = 0; r < 2; r++)
            *(uint4*)(hp + r * 512 + i4 * 8192) = make_uint4(pack_bf16(z[2 * r], z[2 * r + 1]), pack_bf16(z[4 + 2 * r], z[5 + 2 * r]),
                                                                         pack_bf16(z[8 + 2 * r], z[9 + 2 * r]), pack_bf16(z[12 + 2 * r], z[13 + 2 * r]));
    }
}
__device__ __forceinline__ void job_epilogue(float* acc0, float* acc1, int q, int warp, int g, int t) {
    uint8_t* hp = g_h + (size_t)(cta_m() * 72 + job_chunk(job_id(q))) * 16384 + warp * 1024 + g * 64 + ((t ^ (g >> 1)) << 4);
    epilogue_gelu(acc0, hp, q < has_mini() ? mini_w() : 3);
    epilogue_gelu(acc1, hp + 4096, q < has_mini() ? mini_w() : 3);
    kill<96>(acc0); kill<96>(acc1);
    bar_arrive(job_bar(q), 160);
}

__device__ __forceinline__ void epilogue_qkv(const uint32_t* vv, int rg, int g, int t, int wg) {
    const int j = cta_j();
#define V(r, i) vv[2 * (i) + (r)]
    if (wg == 2 && !has_mini()) bar_sync(14, 256);
    uint8_t* p = g_qkv + (size_t)(12 * j) * 98304 + rg * 384 + g * 16;
    const uint32_t pk0 = ((POLYMASK >> (rg & 15)) & 1) ? 0x3f803f80u : 0u, pk1 = ((POLYMASK >> ((rg + 1) & 15)) & 1) ? 0x3f803f80u : 0u;
#pragma unroll
    for (int gi = 0; gi < 3; gi++) {
        const int which = (3 * j + gi) >> 3;
        const uint32_t ec = which == 2 ? 0x00003f80u : 0x427e4740u, ed = which == 2 ? 0u : 0x3aacbe9au, hs = which == 0 ? 0x3f003f00u : 0x3f803f80u;
        const uint32_t ea0 = which == 1 ? pk0 : ec, ea1 = which == 1 ? pk1 : ec, eb0 = which == 1 ? pk0 : ed, eb1 = which == 1 ? pk1 : ed;
        uint32_t mx[2] = {0u, 0u};
#pragma unroll
        for (int h = 4 * gi; h < 4 * gi + 4; h++) {
#pragma unroll
            for (int c = 0; c < 2; c++) {
                const int L0 = 9 * h + 4 * c, k = L0 % 4, i0 = L0 / 4;
                const int off = h * 98304 + c * 128 + ((t - k) & 3) * 4;
                *(uint32_t*)(p + off) = (k == 0 || t >= k) ? V(0, i0) : V(0, i0 + 1);
                *(uint32_t*)(p + off + 384) = (k == 0 || t >= k) ? V(1, i0) : V(1, i0 + 1);
            }
            if (t == (9 * h + 8) % 4) {
                uint32_t u0, u1;
                asm("mul.rn.bf16x2 %0, %1, %2;" : "=r"(u0) : "r"(V(0, (9 * h + 8) / 4)), "r"(hs));
                asm("mul.rn.bf16x2 %0, %1, %2;" : "=r"(u1) : "r"(V(1, (9 * h + 8) / 4)), "r"(hs));
                *(uint4*)(p + h * 98304 + 256) = make_uint4(u0, ea0, eb0, 0u);
                *(uint4*)(p + h * 98304 + 256 + 384) = make_uint4(u1, ea1, eb1, 0u);
            }
#pragma unroll
            for (int r = 0; r < 2; r++) {
                const int b0 = (9 * h) / 4;
                uint32_t a;
                asm("mul.rn.bf16x2 %0, %1, %1;" : "=r"(a) : "r"(V(r, b0)));
                asm("fma.rn.bf16x2 %0, %1, %1, %0;" : "+r"(a) : "r"(V(r, b0 + 1)));
                asm("fma.rn.bf16x2 %0, %1, %1, %0;" : "+r"(a) : "r"(V(r, b0 + 2)));
                asm("max.NaN.bf16x2 %0, %0, %1;" : "+r"(mx[r]) : "r"(a));
            }
        }
        float w0 = bf_lo(mx[0]) + bf_hi(mx[0]), w1 = bf_lo(mx[1]) + bf_hi(mx[1]);
        w0 += __shfl_xor_sync(0xffffffffu, w0, 1); w1 += __shfl_xor_sync(0xffffffffu, w1, 1);
        w0 += __shfl_xor_sync(0xffffffffu, w0, 2); w1 += __shfl_xor_sync(0xffffffffu, w1, 2);
        const uint32_t bb = __reduce_max_sync(0xffffffffu, max(__float_as_uint(w0) & 0x7fffffffu, __float_as_uint(w1) & 0x7fffffffu));
        if ((threadIdx.x & 31) == 0) asm volatile("red.shared.max.u32 [%0], %1;" :: "r"(cl(BMAX_OFF + 4 * gi)), "r"(bb) : "memory");
    }
}

__device__ __forceinline__ uint32_t exp2_fma(float a, float b, uint32_t c3f00, uint32_t c0003) {
    uint32_t s, m, e, r;
    asm("prmt.b32 %0, %1, %2, 0x5410;" : "=r"(s) : "r"(__float_as_uint(a)), "r"(__float_as_uint(b)));
    asm("lop3.b32 %0, %1, 0x007f007f, %2, 0xEA;" : "=r"(m) : "r"(s), "r"(c3f00));
    asm("lop3.b32 %0, %1, 0xff80ff80, %2, 0xEA;" : "=r"(e) : "r"(s), "r"(c0003));
    asm("fma.rn.bf16x2 %0, %1, %2, %3;" : "=r"(r) : "r"(s), "r"(m), "r"(e));
    return r;
}
template<int B0> __device__ __forceinline__ void exps(const float* S, uint32_t* P, uint32_t c3f00, uint32_t c0003) {
#pragma unroll
    for (int i = 0; i < 4; i++) {
        if ((POLYMASK >> (i + B0)) & 1) { P[2 * i] = exp2_fma(S[4 * i], S[4 * i + 1], c3f00, c0003); P[2 * i + 1] = exp2_fma(S[4 * i + 2], S[4 * i + 3], c3f00, c0003); }
        else { P[2 * i] = pack_bf16(ex2(S[4 * i]), ex2(S[4 * i + 1])); P[2 * i + 1] = pack_bf16(ex2(S[4 * i + 2]), ex2(S[4 * i + 3])); }
    }
}
__device__ __forceinline__ void pv(float* O, const uint32_t* X, const uint32_t* Y, uint64_t dv) {
    mma_n24_rs<1>(O, X[0], X[1], X[2], X[3], dv); mma_n24_rs<1>(O, X[4], X[5], X[6], X[7], dv + (768 >> 4));
    mma_n24_rs<1>(O, Y[0], Y[1], Y[2], Y[3], dv + 2 * (768 >> 4)); mma_n24_rs<1>(O, Y[4], Y[5], Y[6], Y[7], dv + 3 * (768 >> 4));
}
constexpr uint64_t STEP2 = (256 >> 4) - ((uint64_t)(128 >> 4) << 16);
__device__ __forceinline__ void qk(float* S, uint64_t dq, uint64_t dk) {
    mma_n64_sk<0>(S, dq, dk);
    mma_n64_sk<1>(S, dq + STEP2, dk + STEP2);
}
__device__ __forceinline__ void qk_rs(float* S, const uint32_t* q, uint64_t dk) {
    mma_n64_rs<0>(S, q[0], q[1], q[2], q[3], dk);
    mma_n64_rs<1>(S, q[4], q[5], q[6], q[7], dk + STEP2);
}
__device__ __forceinline__ int helper_id() {
    const int j = cta_j(), h = cta_m() + 16 * (7 - j);
    return (blockIdx.x < 128 && j >= 6 && h < 4 * XS) ? h : -1;
}
__device__ __forceinline__ int num_tasks() { return blockIdx.x >= 128 ? 32 - XS : (helper_id() >= 0 ? 25 : 24); }
__device__ __forceinline__ void seg_info(int seg, int& rd, int& s0, int& len) {
    const int h = helper_id();
    rd = cta_aidx() + NACTA * (h >= 0 ? seg - 1 : seg); s0 = 0; len = 8;
    if (h >= 0 && seg == 0) { rd = 252 + (h & 3); s0 = h >> 2; len = 1; }
    if (rd >= 252 && h < 0) { s0 = XS; len = 8 - XS; }
}
__device__ __forceinline__ void task_table(int task) {
    int seg = task >> 3, k = task & 7;
    if (helper_id() >= 0 && task >= 1) { seg = 1 + ((task - 1) >> 3); k = (task - 1) & 7; }
    int rd, s0, len; seg_info(seg, rd, s0, len);
    const uint32_t hb = (rd >> 3) * 98304;
    asm volatile("st.shared.v2.u32 [%0], {%1, %2};" :: "r"(cl(TASK_OFF + 8 * task)), "r"(hb + 32 * 98304 + (s0 + k) * 12288),
                 "r"(k == 0 ? hb + (rd & 7) * 12288 + 2 + (seg & 1) : 0) : "memory");
}
__device__ __forceinline__ void kv_load(int task) {
    const float2 e = lds64(TASK_OFF + 8 * task);
    const uint32_t ko = __shfl_sync(0xffffffffu, __float_as_uint(e.x), 0), qo = __shfl_sync(0xffffffffu, __float_as_uint(e.y), 0);
    const int sl = task & 7;
    bulk_load(K_OFF + sl * 12288, g_qkv + ko, 12288, BAR_FULLKV + 8 * sl, qo ? 36864 : 24576);
    bulk_load(V_OFF + sl * 12288, g_qkv + ko + 32 * 98304, 12288, BAR_FULLKV + 8 * sl, 0);
    if (qo) bulk_load((qo & 1) ? Q2_OFF : Q_OFF, g_qkv + (qo & ~3u), 12288, BAR_FULLKV + 8 * sl, 0);
}
__device__ __forceinline__ void kv_refill(int task, int wg, int ntask) {
    const int r = task + 8 - KVLAG;
    if ((r & 3) == wg && r >= 8 && r < ntask) {
        mbar_wait(BAR_EMPTYKV + 8 * (r & 7), ((r >> 3) & 1) ^ 1);
        kv_load(r);
    }
}
__device__ __forceinline__ void publish_all(unsigned* flag0, int stride, int seg, unsigned tag) {
    mbar_wait(BAR_DEP + 8 * (seg & 1), (seg >> 1) & 1);
    if ((threadIdx.x & 31) < 4) st_release(flag0 + (threadIdx.x & 31) * stride, tag);
    __syncwarp();
}

__device__ __forceinline__ void pieces_acquire(int wg, unsigned tag) {
    const int lane = threadIdx.x & 31, r = blockIdx.x - 128;
    int n = 0;
    while (!__all_sync(0xffffffffu, ld_acquire(&g_pflag[(r * 4 + wg) * 8 + lane % XS]) == tag))
        asm volatile("{\n.reg .pred q;\nnanosleep.u32 100;\nsetp.gt.u32 q, %0, 4000000;\n@q trap;\n}" :: "r"(++n));
#pragma unroll 1
    for (int i = lane; i < XS * 64; i += 32)
        asm volatile("prefetch.global.L2 [%0];" :: "l"(g_part + (r * XS * 4 + (i >> 4)) * 512 + wg * 128 + (i & 15) * 8) : "memory");
}

__device__ __forceinline__ void attention(int wg, unsigned tag) {
    const int lane = threadIdx.x & 31, t = lane & 3;
    const int warp = __shfl_sync(0xffffffffu, (threadIdx.x >> 5) & 3, 0);
    const bool elect = (threadIdx.x & 127) == 0;
    constexpr uint64_t dk0 = mkdesc(K_OFF, 128, 384, 0), dv0 = mkdesc(V_OFF, 384, 128, 0);
    const uint32_t zero = (blockIdx.x >> 20) * lane;
    const uint32_t c3f00 = __shfl_sync(0xffffffffu, 0x3f003f00u + zero, 0);
    const uint32_t c0003 = __shfl_sync(0xffffffffu, 0x00030003u + zero, 0);
    unsigned* pending = nullptr; int pstride = 0;
    const int ntask = num_tasks();
    int T = 0;
#pragma unroll 1
    for (int seg = 0; T < ntask; seg++) {
        int rd, s0, len; seg_info(seg, rd, s0, len);
        const int Tend = T + len, Tpub = (seg > 0 && (seg & 3) == wg && ((warp + wg) & 3) == 2) ? (len < 4 ? Tend - 1 : T + 3) : -1;
        mbar_wait(BAR_FULLKV + 8 * (T & 7), (T >> 3) & 1);
        const bool fast = (__shfl_sync(0xffffffffu, lds32(FAST_OFF), 0) >> (rd >> 5)) & 1;
        const uint64_t q = mkdesc(Q_OFF, 128, 384, 0) + (uint64_t)((((seg & 1) ? Q2_OFF - Q_OFF : 0) + wg * 3072) >> 4);
        float m0 = 0.f, m1 = 0.f;
        float SA[32], SB_[32], O[12];
        uint32_t P[16];
#pragma unroll
        for (int i = 0; i < 12; i++) O[i] = 0.f;
        if (!fast) m0 = m1 = -INFINITY;
        if (len != 8 && len != 1) {
            bar_sync(4 + wg, 128);
            float4 pa[XS][4];
#pragma unroll
            for (int i = 0; i < XS; i++) {
                const float4* pp = g_part + ((rd - 252) * XS + i) * 2048 + threadIdx.x;
#pragma unroll
                for (int e = 0; e < 4; e++) pa[i][e] = __ldcg(pp + 512 * e);
            }
#pragma unroll
            for (int i = 0; i < XS; i++) {
                const float4 a = pa[i][0], b = pa[i][1], c = pa[i][2], m = pa[i][3];
                const float n0 = fmaxf(m0, m.x), n1 = fmaxf(m1, m.y);
                const float f0 = ex2(m0 - n0), f1 = ex2(m1 - n1), g0 = ex2(m.x - n0), g1 = ex2(m.y - n1);
                m0 = n0; m1 = n1;
                O[0] = O[0] * f0 + a.x * g0; O[1] = O[1] * f0 + a.y * g0; O[2] = O[2] * f1 + a.z * g1; O[3] = O[3] * f1 + a.w * g1;
                O[4] = O[4] * f0 + b.x * g0; O[5] = O[5] * f0 + b.y * g0; O[6] = O[6] * f1 + b.z * g1; O[7] = O[7] * f1 + b.w * g1;
                O[8] = O[8] * f0 + c.x * g0; O[9] = O[9] * f0 + c.y * g0; O[10] = O[10] * f1 + c.z * g1; O[11] = O[11] * f1 + c.w * g1;
            }
        }
#pragma unroll
        for (int i = 0; i < 12; i++) asm volatile("add.f32 %0, %0, %1;" : "+f"(O[i]) : "f"(__uint_as_float(zero)) : "memory");
        if (fast) {
            uint64_t dk = dk0 + (uint64_t)((T & 7) * (12288 >> 4)), dv = dv0 + (uint64_t)((T & 7) * (12288 >> 4));
            WG_FENCE();
            qk(SA, q, dk); WG_COMMIT();
            qk(SB_, q, dk + (3072 >> 4)); WG_COMMIT();
            dk += 2 * (3072 >> 4);
            const int role = (warp + wg) & 3;
            const uint32_t duty = role == 0 ? ~0u << (T + 1) : (role == 1 ? 0x11111111u << ((wg + KVLAG) & 3) : (Tpub >= 0 ? 1u << Tpub : (role == 3 && blockIdx.x >= 128 ? 1u << 22 : 0u)));
#pragma unroll 1
            for (; T < Tend; T++) {
                const uint32_t wrap = (T & 7) == 7 ? (8 * 12288 >> 4) : 0;
#pragma unroll
                for (int h = 0; h < 4; h++) {
                    float* S = (h & 1) ? SB_ : SA;
                    WG_WAIT(1);
                    keep<32>(S); keep<12>(O);
                    if (h & 1) { exps<8>(S, P, c3f00, c0003); exps<12>(S + 16, P + 8, c3f00, c0003); } else { exps<0>(S, P, c3f00, c0003); exps<4>(S + 16, P + 8, c3f00, c0003); }
                    keep<16>(P);
                    WG_FENCE();
                    pv(O, P, P + 8, dv); WG_COMMIT();
                    qk(S, q, dk); WG_COMMIT();
                    dv += (3072 >> 4); dk += (3072 >> 4);
                    if (h == 1) { dk -= wrap; if (T + 1 < Tend) mbar_wait_raw(cl(BAR_FULLKV) + 8 * ((T + 1) & 7), ((T + 1) >> 3) & 1); }
                    if (h == 3) dv -= wrap;
                    if (h == 0 && ((duty >> T) & 1)) {
                        if (role == 0) { if (lane == 0) mbar_arrive(BAR_EMPTYKV + 8 * ((T - 1) & 7)); __syncwarp(); }
                        else if (role == 1) kv_refill(T, wg, ntask);
                        else if (role == 2) publish_all(pending, pstride, seg - 1, tag);
                        else pieces_acquire(wg, tag);
                    }
                }
            }
            WG_WAIT(0);
            keep<12>(O); keep<32>(SA); keep<32>(SB_);
            m0 = m1 = 0.f;
        } else {
            const uint32_t qa = ((seg & 1) ? Q2_OFF : Q_OFF) + (wg * 8 + warp * 2) * 384 + lane * 4;
            uint32_t qr[8];
            qr[0] = lds32(qa); qr[1] = lds32(qa + 384); qr[2] = lds32(qa + 128); qr[3] = lds32(qa + 384 + 128);
            qr[4] = lds32(qa + 256 + (t ? 12 - 4 * t : 0)); qr[5] = lds32(qa + 384 + 256 + (t ? 12 - 4 * t : 0));
            qr[6] = lds32(qa + 256 + (t ? 12 - 4 * t : 0)); qr[7] = lds32(qa + 384 + 256 + (t ? 12 - 4 * t : 0));
            keep<8>(qr);
#pragma unroll 1
            for (; T < Tend; T++) {
                if (warp == 1) kv_refill(T, wg, ntask);
                if (T == Tpub) publish_all(pending, pstride, seg - 1, tag);
                if (T == 22 && warp == 3 && blockIdx.x >= 128) pieces_acquire(wg, tag);
                mbar_wait(BAR_FULLKV + 8 * (T & 7), (T >> 3) & 1);
#pragma unroll 1
                for (int h = 0; h < 4; h++) {
                    const uint64_t so = (uint64_t)(((T & 7) * 12288 + h * 3072) >> 4);
                    WG_FENCE();
                    qk_rs(SA, qr, dk0 + so); WG_COMMIT();
                    WG_WAIT(0);
                    keep<32>(SA); keep<12>(O);
                    float n0 = m0, n1 = m1;
#pragma unroll
                    for (int i = 0; i < 8; i++) { n0 = fmaxf(n0, fmaxf(SA[4 * i], SA[4 * i + 1])); n1 = fmaxf(n1, fmaxf(SA[4 * i + 2], SA[4 * i + 3])); }
                    n0 = fmaxf(n0, __shfl_xor_sync(0xffffffffu, n0, 1)); n0 = fmaxf(n0, __shfl_xor_sync(0xffffffffu, n0, 2));
                    n1 = fmaxf(n1, __shfl_xor_sync(0xffffffffu, n1, 1)); n1 = fmaxf(n1, __shfl_xor_sync(0xffffffffu, n1, 2));
                    const float f0 = ex2(m0 - n0), f1 = ex2(m1 - n1);
                    m0 = n0; m1 = n1;
#pragma unroll
                    for (int i = 0; i < 3; i++) { O[4 * i] *= f0; O[4 * i + 1] *= f0; O[4 * i + 2] *= f1; O[4 * i + 3] *= f1; }
#pragma unroll
                    for (int i = 0; i < 8; i++) {
                        P[2 * i] = pack_bf16(ex2(SA[4 * i] - m0), ex2(SA[4 * i + 1] - m0));
                        P[2 * i + 1] = pack_bf16(ex2(SA[4 * i + 2] - m1), ex2(SA[4 * i + 3] - m1));
                    }
                    keep<16>(P); keep<12>(O);
                    WG_FENCE();
                    pv(O, P, P + 8, dv0 + so); WG_COMMIT();
                    WG_WAIT(0);
                    keep<12>(O);
                }
                if (elect && T + 1 < Tend) mbar_arrive(BAR_EMPTYKV + 8 * (T & 7));
            }
        }
        if (elect) mbar_arrive(BAR_EMPTYKV + 8 * ((T - 1) & 7));
        if (wg == 1) TS2(4 + seg);
        if (len == 1) {
            float4* pp = g_part + ((rd - 252) * XS + s0) * 2048 + threadIdx.x;
            pp[0] = make_float4(O[0], O[1], O[2], O[3]); pp[512] = make_float4(O[4], O[5], O[6], O[7]);
            pp[1024] = make_float4(O[8], O[9], O[10], O[11]); pp[1536] = make_float4(m0, m1, 0.f, 0.f);
            pending = &g_pflag[(rd - 252) * 32 + s0]; pstride = 8;
            __syncwarp();
            if (lane == 0) mbar_arrive(BAR_DEP + 8 * (seg & 1));
            continue;
        }
        const int head = rd >> 3, rb = (rd & 7) * 4 + wg, g = lane >> 2;
        const float l0 = __shfl_sync(0xffffffffu, O[8], (lane & ~3) | 1), l1 = __shfl_sync(0xffffffffu, O[10], (lane & ~3) | 1);
        const float r0 = 2.0f * __frcp_rn(l0), r1 = 2.0f * __frcp_rn(l1);
        uint8_t* ob = g_o + (size_t)(rb >> 1) * (9 * 16384) + ((rb & 1) * 8 + warp * 2) * 1024 + g * 16;
        uint8_t* op = ob + (head >> 2) * 16384 + (head & 3) * 256 + t * 4;
#pragma unroll
        for (int i = 0; i < 2; i++) {
            *(uint32_t*)(op + i * 128) = pack_bf16(O[4 * i] * r0, O[4 * i + 1] * r0);
            *(uint32_t*)(op + i * 128 + 1024) = pack_bf16(O[4 * i + 2] * r1, O[4 * i + 3] * r1);
        }
        if (t == 0) {
            uint8_t* ol = ob + 8 * 16384 + (head >> 2) * 128 + (head & 3) * 4;
            *(uint32_t*)ol = pack_bf16(O[8] * r0, O[9] * r0); *(uint32_t*)(ol + 1024) = pack_bf16(O[10] * r1, O[11] * r1);
        }
        pending = &g_oflag[(rd & 7) * 128 + head]; pstride = 32;
        __syncwarp();
        if (lane == 0) mbar_arrive(BAR_DEP + 8 * (seg & 1));
    }
    bar_sync(4 + wg, 128);
    if (elect) st_release(pending + wg * pstride, tag);
}

__global__ void __cluster_dims__(2, 1, 1) __launch_bounds__(NTHREADS, 1) fused_kernel(const __grid_constant__ Params p) {
    extern __shared__ __align__(1024) uint8_t smem_raw[];
    if ((uint32_t)__cvta_generic_to_shared(smem_raw) != cl(SB)) asm volatile("trap;");
    const int wg = __shfl_sync(0xffffffffu, threadIdx.x >> 7, 0);
    const int lane = threadIdx.x & 31;
    const bool elect = (threadIdx.x & 127) == 0;
    const bool gemm = blockIdx.x < 128;
    const bool five = cta_j() == 2 || cta_j() == 5;
    if (threadIdx.x >= 32 && threadIdx.x < 42) asm volatile("prefetch.tensormap [%0];" :: "l"(&p.wq4 + (threadIdx.x - 32)) : "memory");
    const int lrow = (blockIdx.x & 1) * 64 + (threadIdx.x >> 3);
    uint32_t v[36];
    if (gemm) {
        const uint4* xr = (const uint4*)(p.xp + (size_t)(cta_m() * 128 + lrow) * DM) + (lane & 7);
#pragma unroll
        for (int i = 0; i < 9; i++) { const uint4 w = __ldg(xr + i * 8); v[4 * i] = w.x; v[4 * i + 1] = w.y; v[4 * i + 2] = w.z; v[4 * i + 3] = w.w; }
        if (threadIdx.x >= 384 && threadIdx.x < 506 && blockIdx.x * 15616 + (threadIdx.x - 384) * 128 < 1728 * DM * 2)
            asm volatile("prefetch.global.L2 [%0];" :: "l"((const uint8_t*)p.wqkvp + blockIdx.x * 15616 + (threadIdx.x - 384) * 128) : "memory");
    }
    if ((threadIdx.x & 31) < NBARS / 16) {
        const int i = (threadIdx.x >> 5) * (NBARS / 16) + (threadIdx.x & 31);
        const uint32_t cnt = (i >= 55 && i < 64) || i == 79 ? 2 : (i >= 38 && i < 46 ? 4 : ((i == 66 || i == 67) && !cta_isG() ? 16 : 1));
        mbar_init(BAR_OFF + 8 * i, cnt);
        asm volatile("fence.mbarrier_init.release.cluster;" ::: "memory");
    }
    if (threadIdx.x >= 40 && threadIdx.x < 43) asm volatile("st.shared.u32 [%0], %1;" :: "r"(cl(BMAX_OFF + 4 * (threadIdx.x - 40))), "r"(0) : "memory");
    __syncthreads();
    asm volatile("barrier.cluster.arrive.relaxed.aligned;" ::: "memory");
    TS(wg);
    if (gemm) {
        const int ks = __shfl_sync(0xffffffffu, threadIdx.x >> 5, 0);
        if (ks < (five ? 7 : 9)) {
            const int st = five ? (ks == 0 ? 6 : ks - 1) : ks;
            if (five && ks > 0 && lane < 3) mbar_arrive(lane == 0 ? BAR_FULLW + 8 * st : BAR_EMPTYW + 8 * st);
            __syncwarp();
            tma3d(B_OFF + st * (five ? 10240 : 8192), five ? &p.wq5 : &p.wq4, ks * 16, (216 * cta_j()) >> 6, BAR_FULLW + 8 * st, five ? 10240 : 8192);
        }
        float f[72], s = 0.f, s2 = 0.f;
#pragma unroll
        for (int i = 0; i < 36; i++) { f[2 * i] = bf_lo(v[i]); f[2 * i + 1] = bf_hi(v[i]); s += f[2 * i]; s2 += f[2 * i + 1]; }
        s += s2;
        s += __shfl_xor_sync(0xffffffffu, s, 1); s += __shfl_xor_sync(0xffffffffu, s, 2); s += __shfl_xor_sync(0xffffffffu, s, 4);
        const float mean = s * (1.0f / DM);
        if (wg == 1) TS(29);
        float q = 0.f, q2 = 0.f;
#pragma unroll
        for (int i = 0; i < 36; i++) { f[2 * i] -= mean; f[2 * i + 1] -= mean; q = fmaf(f[2 * i], f[2 * i], q); q2 = fmaf(f[2 * i + 1], f[2 * i + 1], q2); }
        q += q2;
        q += __shfl_xor_sync(0xffffffffu, q, 1); q += __shfl_xor_sync(0xffffffffu, q, 2); q += __shfl_xor_sync(0xffffffffu, q, 4);
        const float rstd = rsqrtf(q * (1.0f / DM) + 1e-5f);
        const uint32_t dst = cl(A_OFF + lrow * 128 + (((lane & 7) ^ (lrow & 7)) << 4));
#pragma unroll
        for (int i = 0; i < 9; i++)
            asm volatile("st.shared.v4.b32 [%0], {%1,%2,%3,%4};" :: "r"(dst + i * 16384),
                "r"(pack_bf16(f[8 * i] * rstd, f[8 * i + 1] * rstd)), "r"(pack_bf16(f[8 * i + 2] * rstd, f[8 * i + 3] * rstd)),
                "r"(pack_bf16(f[8 * i + 4] * rstd, f[8 * i + 5] * rstd)), "r"(pack_bf16(f[8 * i + 6] * rstd, f[8 * i + 7] * rstd)) : "memory");
        if (wg == 1) TS(31);
        asm volatile("fence.proxy.async.shared::cta;" ::: "memory");
    }
    asm volatile("barrier.cluster.wait.aligned;" ::: "memory");
    __syncthreads();
    if (gemm && threadIdx.x < 32) { send_half(0); send_half(1); }
    TS(28);

    if (wg == 0) {
        asm volatile("setmaxnreg.dec.sync.aligned.u32 24;");
        const int warp = __shfl_sync(0xffffffffu, threadIdx.x >> 5, 0);
        if (warp == 0) {
            if (gemm) {
                int st = five ? 6 : 0; uint32_t ph = 0;
                const int nst = five ? 7 : 9; const uint32_t sb = five ? 10240 : 8192;
#pragma unroll 1
                for (int ks = nst; ks < 36; ks++) {
                    const int i = ks - nst;
                    if ((i % 3) == 0 && i < 21) send_half(2 + i / 3);
                    mbar_wait(BAR_EMPTYW + 8 * st, ph);
                    tma3d(B_OFF + st * sb, five ? &p.wq5 : &p.wq4, ks * 16, (216 * cta_j()) >> 6, BAR_FULLW + 8 * st, sb);
                    if (++st == nst) { st = 0; ph ^= 1; }
                }
                st = 0; ph = 1;
                int fresh = 6;
#pragma unroll 1
                for (int q = 0; q < num_jobs(); q++) {
#pragma unroll 1
                    for (int k = 0; k < DM; k += (q < has_mini() ? (mini_w() == 1 ? 96 : 48) : 32)) {
                        if (fresh) { fresh--; mbar_wait(BAR_EMPTYW + 8 * (five ? (st == 5 ? 6 : st + 1) : (3 * st + 2) >> 1), 1); }
                        else mbar_wait(BAR_EMPTYB + 8 * st, ph);
                        tma3d(B_OFF + st * 12288, q < has_mini() ? (mini_w() == 1 ? &p.w1n : &p.w1m) : &p.w1, k, job_chunk(job_id(q)), BAR_FULLB + 8 * st, 12288);
                        if (++st == 6) { st = 0; ph ^= 1; }
                    }
                }
                if (cta_isG()) {
#pragma unroll 1
                    for (int hk = 0; hk < 162; hk++) {
                        mbar_wait(BAR_EMPTYB + 8 * st, ph);
                        if (hk < 144) tma5d(B_OFF + st * 12288, &p.w2, (hk >> 1) * 32 + (hk & 1) * 4, cta_j() * 3, BAR_FULLB + 8 * st, 12288);
                        else tma4d(B_OFF + st * 12288, hk < 160 ? &p.wo : &p.wol, hk < 160 ? 0 : 16, hk < 160 ? (hk - 144) * 2 : (hk - 160) * 16, cta_j() * 3, BAR_FULLB + 8 * st, 12288);
                        if (++st == 6) { st = 0; ph ^= 1; }
                    }
                }
            }
        } else if (warp == 1) {
            if (gemm) {
                const unsigned tag = get_tag();
                bar_sync(10, 288);
                if (lane < 3) atomicMax(&g_bound[(3 * cta_j() + lane) * 16], ((unsigned long long)tag << 32) | lds32(BMAX_OFF + 4 * lane));
                __syncwarp();
                if (lane == 0) red_release(&g_qkvcnt, 1);
                __syncwarp();
#pragma unroll 1
                for (int q = 0; q < num_jobs(); q++) {
                    bar_sync(job_bar(q), 160);
                    if (lane < (q < has_mini() ? mini_w() : 1)) st_release(&g_hflag[cta_m() * 32 + job_id(q) + lane], tag);
                    __syncwarp();
                }
            }
        } else if (warp == 3) {
            if (cta_isG()) {
                int sa = 0, dep = 0, next_dep = 0; uint32_t pa = 0;
#pragma unroll 1
                for (int kk = 0; kk < 84; kk++) {
                    if (kk == next_dep) {
                        mbar_wait(BAR_DEP + 8 * dep, 0);
                        dep++;
                        next_dep = kk < 63 ? (kk == 0 ? 30 : (kk == 30 ? 54 : 63)) : (kk == 63 ? 75 : kk + 1);
                    }
                    mbar_wait(BAR_EMPTYA + 8 * sa, pa);
                    if (kk >= 72 && kk < 75) tma2d(A_OFF + sa * 16384, &p.x, (3 * cta_j() + kk - 72) * 64, cta_m() * 128, BAR_FULLA + 8 * sa, 16384);
                    else bulk_load(A_OFF + sa * 16384, kk < 72 ? g_h + (size_t)(cta_m() * 72 + kk) * 16384 : g_o + (size_t)(cta_m() * 9 + (kk - 75)) * 16384, 16384, BAR_FULLA + 8 * sa, 16384);
                    if (++sa == 9) { sa = 0; pa ^= 1; }
                }
            } else {
                const unsigned tag = get_tag();
                task_table(lane);
                if (gemm) mbar_wait(BAR_WDONE, 0);
                flag_wait(&g_qkvcnt, tag * 128);
                __syncwarp();
                const float bn = lane < 24 ? __uint_as_float((uint32_t)ld_tagged(&g_bound[lane * 16])) * 1.02f : 0.f;
                asm volatile("fence.proxy.async.global;" ::: "memory");
                const float bk = __shfl_sync(0xffffffffu, bn, (lane & 7) + 8), bv = __shfl_sync(0xffffffffu, bn, (lane & 7) + 16);
                const uint32_t fastmask = __ballot_sync(0xffffffffu, __fsqrt_rn(bn * bk) + 0.5f * __log2f(fmaxf(bv, 1.0f)) <= GUARD);
                asm volatile("st.shared.u32 [%0], %1;" :: "r"(cl(FAST_OFF)), "r"(fastmask) : "memory");
                __syncwarp();
#pragma unroll 1
                for (int s = 0; s < 8; s++) {
                    if (gemm) mbar_wait(BAR_EMPTYA + 8 * (s == 0 ? 7 : 8), 0);
                    kv_load(s);
                }
            }
        } else {
            if (gemm) l2_prefetch((const uint8_t*)p.w1p + blockIdx.x * 41472, 41472, 300);
            else {
                asm volatile("nanosleep.u32 4000;");
#pragma unroll 1
                for (int i = 0; i < 36; i++) {
                    if (i < 32) l2_prefetch_bulk((const uint8_t*)p.w2p + (i * 4 + (blockIdx.x - 128)) * 41472, 41472);
                    else l2_prefetch_bulk((const uint8_t*)p.wop + ((i - 32) * 4 + (blockIdx.x - 128)) * 41472, 41472);
                }
            }
            if (cta_isG()) {
                const unsigned tag = get_tag();
                mbar_wait(BAR_WDONE, 0);
#pragma unroll 1
                for (int d = 0; d < 4; d++) {
                    if (lane < (d == 0 ? 14 : 19 + 3 * d)) flag_wait(&g_hflag[cta_m() * 32 + lane], tag);
                    __syncwarp();
                    fence_async();
                    if (lane == 0) mbar_arrive(BAR_DEP + 8 * d);
                }
                int d = 0, n = 0;
                const unsigned* f0 = &g_oflag[(cta_m() * 2) * 32 + lane];
#pragma unroll 1
                while (d < 9) {
                    unsigned a, b;
                    asm volatile("ld.acquire.gpu.global.u32 %0, [%1];" : "=r"(a) : "l"(f0) : "memory");
                    asm volatile("ld.acquire.gpu.global.u32 %0, [%1];" : "=r"(b) : "l"(f0 + 32) : "memory");
                    const uint32_t miss = ~__ballot_sync(0xffffffffu, a == tag && b == tag);
                    const int ready = miss ? (__ffs(miss) - 1) >> 2 : 9;
                    if (ready > d) {
                        asm volatile("fence.proxy.async.global;" ::: "memory");
                        if (lane >= d && lane < ready) mbar_arrive(BAR_DEP + 8 * (4 + lane));
                        d = ready;
                    } else asm volatile("{\n.reg .pred q;\nnanosleep.u32 %1;\nsetp.gt.u32 q, %0, 4000000;\n@q trap;\n}" :: "r"(++n), "r"(d < 5 ? 500 : 20));
                }
            }
        }
        if (cta_isG()) {
            bar_sync(4, 128);
            if (elect) red_relaxed(&g_done, 1);
            return;
        }
        bar_sync(2, 256);
        asm volatile("setmaxnreg.inc.sync.aligned.u32 128;");
    } else if (wg == 3) {
        asm volatile("setmaxnreg.dec.sync.aligned.u32 24;");
        if (gemm) {
            const int tid = threadIdx.x & 127;
#pragma unroll 2
            for (int w = tid; w < 1024; w += 128) {
                uint32_t bw, bdst;
                if (w < 768) {
                    const int c = w >> 8, r = (w >> 5) & 7, k = w & 31;
                    bw = (r < num_jobs() && (r >= has_mini() || c < mini_w())) ? __ldg((const uint32_t*)p.b1p + (job_chunk(job_id(r)) + c) * 32 + k) : 0u;
                    if (r == 5 && cta_isG()) bw = __ldg((const uint32_t*)p.b2p + (3 * cta_j() + c) * 32 + k);
                    bdst = BIAS_OFF + c * 1024 + r * 128 + (((k >> 2) ^ r) << 4) + (k & 3) * 4;
                } else {
                    const int u = w - 768, q = u >> 5, k = u & 3;
                    bw = (q < 6 && k == (q >> 1)) ? (q == 5 ? 0x40000000u : ((q & 1) ? 0x3f800000u : 0x00003f80u)) : 0u;
                    bdst = ONE_OFF + u * 4;
                }
                asm volatile("st.shared.u32 [%0], %1;" :: "r"(cl(bdst)), "r"(bw) : "memory");
            }
            asm volatile("fence.proxy.async.shared::cta;" ::: "memory");
            bar_sync(7, 128);
            if (elect) mbar_arrive(BAR_INFO);
        }
        if (cta_isG()) {
            if (elect) red_relaxed(&g_done, 1);
            return;
        }
        bar_sync(1, 256);
        asm volatile("setmaxnreg.inc.sync.aligned.u32 128;");
    } else {
        const int warp = __shfl_sync(0xffffffffu, (threadIdx.x >> 5) & 3, 0), g = lane >> 2, t = lane & 3;
        asm volatile("setmaxnreg.inc.sync.aligned.u32 232;");
        if (gemm) {
            uint32_t vv[54];
            switch (cta_j()) {
                case 0: qkv_mainloop<0>(vv, wg, elect); break;
                case 1: qkv_mainloop<1>(vv, wg, elect); break;
                case 2: qkv_mainloop<2>(vv, wg, elect); break;
                case 3: qkv_mainloop<3>(vv, wg, elect); break;
                case 4: qkv_mainloop<4>(vv, wg, elect); break;
                case 5: qkv_mainloop<5>(vv, wg, elect); break;
                case 6: qkv_mainloop<6>(vv, wg, elect); break;
                default: qkv_mainloop<7>(vv, wg, elect); break;
            }
            if (wg == 1) TS(26);
            float acc0[96], acc1[96];
            kill<96>(acc0); kill<96>(acc1);
            mbar_wait(BAR_INFO, 0);
            mbar_wait(BAR_WDONE, 0);
            keep<54>(vv);
            if (wg == 1 && has_mini()) { if (mini_w() == 1) mini_mainloop<1>(acc0, acc1, elect); else mini_mainloop<2>(acc0, acc1, elect); TS(17); }
            keep<54>(vv);
            epilogue_qkv(vv, cta_m() * 16 + (wg - 1) * 8 + warp * 2, g, t, wg);
            if (wg == 1 && !has_mini()) bar_arrive(14, 256);
            TS(wg == 1 ? 27 : 30);
            bar_arrive(10, 288);
#pragma unroll 1
            for (int q = wg - 1; q < num_jobs() + cta_isG(); q += 2) {
                const bool g2 = q == num_jobs();
                const uint32_t xa = A_OFF + (warp * 16 + (lane & 15)) * 128 + (((lane >> 4) ^ (lane & 7)) << 4);
                if (g2) TS2(9);
                if (q >= has_mini()) job_mainloop(acc0, acc1, q, g2, xa, elect);
                if (g2) {
                    TS2(12);
#pragma unroll
                    for (int c = 0; c < 3; c++) {
#pragma unroll
                        for (int i2 = 4 * c; i2 < 4 * c + 4; i2++) {
#pragma unroll
                            for (int mh = 0; mh < 2; mh++) {
                                const float* a = (mh ? acc1 : acc0) + 8 * i2;
                                asm volatile("stmatrix.sync.aligned.m8n8.x4.shared.b16 [%0], {%1,%2,%3,%4};"
                                    :: "r"(cl((xa ^ ((i2 & 3) << 5)) + (3 + c) * 16384 + mh * 8192)),
                                       "r"(half_bf16(a[0], a[1])), "r"(half_bf16(a[2], a[3])), "r"(half_bf16(a[4], a[5])), "r"(half_bf16(a[6], a[7])) : "memory");
                            }
                        }
                        asm volatile("fence.proxy.async.shared::cta;" ::: "memory");
                        bar_sync(4 + wg, 128);
                        if (elect) asm volatile("cp.async.bulk.tensor.2d.global.shared::cta.bulk_group [%0, {%1, %2}], [%3];"
                                        :: "l"(&p.outm), "r"(cta_j() * 192 + c * 64), "r"(cta_m() * 128), "r"(cl(A_OFF + (3 + c) * 16384)) : "memory");
                    }
                    if (elect) asm volatile("cp.async.bulk.commit_group;\ncp.async.bulk.wait_group.read 0;" ::: "memory");
                    TS2(14);
                    break;
                }
                if (q >= has_mini()) TS(17 + (q < 4 ? q : 4));
                job_epilogue(acc0, acc1, q, warp, g, t);
                TS(22 + (q < 3 ? q : 3));
            }
        }
        if (cta_isG()) {
            bar_sync(4 + wg, 128);
            if (elect) red_relaxed(&g_done, 1);
            return;
        }
        asm volatile("setmaxnreg.dec.sync.aligned.u32 128;");
        bar_arrive(has_mini() ? 3 - wg : wg, 256);
    }
    __syncwarp();
    TS2(8 + wg);
    attention(wg, get_tag());
    TS2(12 + wg);
    bar_sync(4 + wg, 128);
    if (elect) red_relaxed(&g_done, 1);
}

typedef CUresult (*EncFn)(CUtensorMap*, CUtensorMapDataType, cuuint32_t, void*, const cuuint64_t*, const cuuint64_t*, const cuuint32_t*,
                          const cuuint32_t*, CUtensorMapInterleave, CUtensorMapSwizzle, CUtensorMapL2promotion, CUtensorMapFloatOOBfill);

void make_map(EncFn enc, CUtensorMap* m, const void* ptr, int rank, const cuuint64_t* dims, const cuuint64_t* strides, const cuuint32_t* box) {
    cuuint32_t es[5] = {1, 1, 1, 1, 1};
    enc(m, CU_TENSOR_MAP_DATA_TYPE_BFLOAT16, rank, const_cast<void*>(ptr), dims, strides, box, es, CU_TENSOR_MAP_INTERLEAVE_NONE,
        CU_TENSOR_MAP_SWIZZLE_128B, L2PROMO, CU_TENSOR_MAP_FLOAT_OOB_FILL_NONE);
}
void make_act_map(EncFn enc, CUtensorMap* m, const void* ptr, int cols) {
    cuuint64_t d[2] = {(cuuint64_t)cols, SEQ}, s[1] = {(cuuint64_t)cols * 2}; cuuint32_t b[2] = {64, 128};
    make_map(enc, m, ptr, 2, d, s, b);
}

}

extern "C" void kernel_launch(void* const* d_in, const int* in_sizes, int n_in, void* d_out, int out_size) {
    static Params prm;
    static bool ready = false;
    static const void* key[9];
    bool same = ready && key[8] == d_out;
    for (int i = 0; i < 8 && same; i++) same = key[i] == d_in[i];
    if (!same) {
        EncFn enc = nullptr; cudaDriverEntryPointQueryResult qr;
        cudaGetDriverEntryPoint("cuTensorMapEncodeTiled", (void**)&enc, cudaEnableDefault, &qr);
        make_act_map(enc, &prm.outm, d_out, DM);
        make_act_map(enc, &prm.x, d_in[0], DM);
        {
            cuuint64_t d[3] = {64, DM, 27}, s[2] = {1728 * 2, 128}; cuuint32_t b4[3] = {64, 16, 4}, b5[3] = {64, 16, 5};
            make_map(enc, &prm.wq4, d_in[1], 3, d, s, b4);
            make_map(enc, &prm.wq5, d_in[1], 3, d, s, b5);
        }
        {
            cuuint64_t d[3] = {64, DM, FF / 64}, s[2] = {FF * 2, 128}; cuuint32_t b[3] = {64, 32, 3};
            make_map(enc, &prm.w1, d_in[4], 3, d, s, b);
            cuuint32_t bn[3] = {64, 96, 1};
            make_map(enc, &prm.w1n, d_in[4], 3, d, s, bn);
            cuuint32_t bm[3] = {64, 48, 2};
            make_map(enc, &prm.w1m, d_in[4], 3, d, s, bm);
        }
        {
            cuuint64_t d[4] = {64, 18, NH, DM / 64}, s[3] = {DM * 2, 18 * DM * 2, 128}; cuuint32_t b0[4] = {64, 16, 2, 3}, b1[4] = {64, 2, 16, 3};
            make_map(enc, &prm.wo, d_in[2], 4, d, s, b0);
            make_map(enc, &prm.wol, d_in[2], 4, d, s, b1);
        }
        {
            cuuint64_t d[5] = {64, 2, 4, 2280, DM / 64}, s[4] = {DM * 2, 16 * DM * 2, 2 * DM * 2, 128}; cuuint32_t b[5] = {64, 2, 4, 4, 3};
            make_map(enc, &prm.w2, d_in[6], 5, d, s, b);
        }
        prm.xp = (const __nv_bfloat16*)d_in[0]; prm.wqkvp = (const __nv_bfloat16*)d_in[1]; prm.w1p = (const __nv_bfloat16*)d_in[4];
        prm.b1p = (const __nv_bfloat16*)d_in[5]; prm.b2p = (const __nv_bfloat16*)d_in[7]; prm.out = (__nv_bfloat16*)d_out;
        prm.w2p = (const __nv_bfloat16*)d_in[6]; prm.wop = (const __nv_bfloat16*)d_in[2];
        cudaFuncSetAttribute(fused_kernel, cudaFuncAttributeMaxDynamicSharedMemorySize, SMEM_BYTES);
        for (int i = 0; i < 8; i++) key[i] = d_in[i];
        key[8] = d_out; ready = true;
    }
    fused_kernel<<<NCTA, NTHREADS, SMEM_BYTES, cudaStreamPerThread>>>(prm);
}
```

```cpp
#include <cuda_runtime.h>
#include <cuda_bf16.h>
#include <cuda.h>
#include <stdint.h>

#define L2PROMO CU_TENSOR_MAP_L2_PROMOTION_L2_128B
namespace {

constexpr int SEQ = 2048, DM = 576, FF = 4608, NH = 32;
constexpr int NCTA = 132, NTHREADS = 512, NACTA = 84;
#define GUARD 80.0f
#define HELP2 5
#define KVLAG 5
#define PMASK 0xAD6Bu
constexpr uint32_t POLYMASK = PMASK;

constexpr uint32_t SB = 0x400;
constexpr uint32_t A_OFF = SB;
constexpr uint32_t B_OFF = SB + 9 * 16384;
constexpr uint32_t Q_OFF = SB, Q2_OFF = SB + 12288 + 8 * 24576;
constexpr uint32_t K_OFF = SB + 12288, V_OFF = K_OFF + 8 * 12288;
constexpr uint32_t BAR_OFF = B_OFF + 6 * 12288;
constexpr uint32_t BAR_FULLA = BAR_OFF, BAR_EMPTYA = BAR_FULLA + 72, BAR_FULLB = BAR_EMPTYA + 72, BAR_EMPTYB = BAR_FULLB + 48,
                   BAR_FULLKV = BAR_EMPTYB + 48, BAR_EMPTYKV = BAR_FULLKV + 64, BAR_FULLW = BAR_EMPTYKV + 64, BAR_EMPTYW = BAR_FULLW + 72,
                   BAR_INFO = BAR_EMPTYW + 72, BAR_DEP = BAR_INFO + 16, BAR_WDONE = BAR_DEP + 13 * 8, FAST_OFF = BAR_WDONE + 8, BMAX_OFF = FAST_OFF + 4;
constexpr int NBARS = 9 + 9 + 6 + 6 + 8 + 8 + 9 + 9 + 2 + 13 + 1;
static_assert(NBARS % 16 == 0, "barrier init");
constexpr uint32_t ONE_OFF = BAR_OFF + 768;
constexpr uint32_t BIAS_OFF = BAR_OFF + 2048;
constexpr uint32_t TASK_OFF = BIAS_OFF + 3072;
constexpr uint32_t SMEM_END = TASK_OFF + 256;
static_assert(ONE_OFF + 1024 <= BIAS_OFF && BIAS_OFF % 1024 == 0, "smem map");
constexpr uint32_t SMEM_BYTES = SMEM_END - SB;
static_assert(SMEM_BYTES <= 232448, "smem");

__device__ __align__(1024) uint8_t g_h[SEQ * FF * 2];
__device__ __align__(1024) uint8_t g_o[SEQ * DM * 2];
__device__ __align__(1024) uint8_t g_qkv[96 * 98304];
__device__ unsigned long long g_bound[24 * 16];
__device__ unsigned g_done;
__device__ unsigned g_qkvcnt;
__device__ unsigned g_hflag[16 * 32];
#define XS 6
__device__ __align__(16) float4 g_part[4 * XS * 4 * 512];
__device__ unsigned g_pflag[4 * 4 * 8];
__device__ unsigned g_oflag[32 * 32];
#define TS(i)
#define TS2(i)

struct Params {
    const __nv_bfloat16* xp; const __nv_bfloat16* wqkvp; const __nv_bfloat16* w1p; const __nv_bfloat16* b1p; const __nv_bfloat16* b2p;
    const __nv_bfloat16* w2p; const __nv_bfloat16* wop;
    __nv_bfloat16* out;
    CUtensorMap wq4, wq5, w1n, w1m, w1, w2, wo, x, outm;
};

template<int N> __device__ __forceinline__ void mma_ssp(float* d, uint64_t da, uint64_t db, int sd);
template<> __device__ __forceinline__ void mma_ssp<8>(float* d, uint64_t da, uint64_t db, int sd) {
    asm volatile("{\n.reg .pred p;\nsetp.ne.b32 p, %6, 0;\nwgmma.mma_async.sync.aligned.m64n8k16.f32.bf16.bf16 {%0,%1,%2,%3}, %4, %5, p, 1, 1, 0, 1;\n}\n"
      : "+f"(d[0]),"+f"(d[1]),"+f"(d[2]),"+f"(d[3])
      : "l"(da), "l"(db), "r"(sd));
}
template<> __device__ __forceinline__ void mma_ssp<16>(float* d, uint64_t da, uint64_t db, int sd) {
    asm volatile("{\n.reg .pred p;\nsetp.ne.b32 p, %10, 0;\nwgmma.mma_async.sync.aligned.m64n16k16.f32.bf16.bf16 {%0,%1,%2,%3,%4,%5,%6,%7}, %8, %9, p, 1, 1, 0, 1;\n}\n"
      : "+f"(d[0]),"+f"(d[1]),"+f"(d[2]),"+f"(d[3]),"+f"(d[4]),"+f"(d[5]),"+f"(d[6]),"+f"(d[7])
      : "l"(da), "l"(db), "r"(sd));
}
template<> __device__ __forceinline__ void mma_ssp<24>(float* d, uint64_t da, uint64_t db, int sd) {
    asm volatile("{\n.reg .pred p;\nsetp.ne.b32 p, %14, 0;\nwgmma.mma_async.sync.aligned.m64n24k16.f32.bf16.bf16 {%0,%1,%2,%3,%4,%5,%6,%7,%8,%9,%10,%11}, %12, %13, p, 1, 1, 0, 1;\n}\n"
      : "+f"(d[0]),"+f"(d[1]),"+f"(d[2]),"+f"(d[3]),"+f"(d[4]),"+f"(d[5]),"+f"(d[6]),"+f"(d[7]),"+f"(d[8]),"+f"(d[9]),"+f"(d[10]),"+f"(d[11])
      : "l"(da), "l"(db), "r"(sd));
}
template<> __device__ __forceinline__ void mma_ssp<32>(float* d, uint64_t da, uint64_t db, int sd) {
    asm volatile("{\n.reg .pred p;\nsetp.ne.b32 p, %18, 0;\nwgmma.mma_async.sync.aligned.m64n32k16.f32.bf16.bf16 {%0,%1,%2,%3,%4,%5,%6,%7,%8,%9,%10,%11,%12,%13,%14,%15}, %16, %17, p, 1, 1, 0, 1;\n}\n"
      : "+f"(d[0]),"+f"(d[1]),"+f"(d[2]),"+f"(d[3]),"+f"(d[4]),"+f"(d[5]),"+f"(d[6]),"+f"(d[7]),"+f"(d[8]),"+f"(d[9]),"+f"(d[10]),"+f"(d[11]),"+f"(d[12]),"+f"(d[13]),"+f"(d[14]),"+f"(d[15])
      : "l"(da), "l"(db), "r"(sd));
}
template<> __device__ __forceinline__ void mma_ssp<40>(float* d, uint64_t da, uint64_t db, int sd) {
    asm volatile("{\n.reg .pred p;\nsetp.ne.b32 p, %22, 0;\nwgmma.mma_async.sync.aligned.m64n40k16.f32.bf16.bf16 {%0,%1,%2,%3,%4,%5,%6,%7,%8,%9,%10,%11,%12,%13,%14,%15,%16,%17,%18,%19}, %20, %21, p, 1, 1, 0, 1;\n}\n"
      : "+f"(d[0]),"+f"(d[1]),"+f"(d[2]),"+f"(d[3]),"+f"(d[4]),"+f"(d[5]),"+f"(d[6]),"+f"(d[7]),"+f"(d[8]),"+f"(d[9]),"+f"(d[10]),"+f"(d[11]),"+f"(d[12]),"+f"(d[13]),"+f"(d[14]),"+f"(d[15]),"+f"(d[16]),"+f"(d[17]),"+f"(d[18]),"+f"(d[19])
      : "l"(da), "l"(db), "r"(sd));
}
template<> __device__ __forceinline__ void mma_ssp<48>(float* d, uint64_t da, uint64_t db, int sd) {
    asm volatile("{\n.reg .pred p;\nsetp.ne.b32 p, %26, 0;\nwgmma.mma_async.sync.aligned.m64n48k16.f32.bf16.bf16 {%0,%1,%2,%3,%4,%5,%6,%7,%8,%9,%10,%11,%12,%13,%14,%15,%16,%17,%18,%19,%20,%21,%22,%23}, %24, %25, p, 1, 1, 0, 1;\n}\n"
      : "+f"(d[0]),"+f"(d[1]),"+f"(d[2]),"+f"(d[3]),"+f"(d[4]),"+f"(d[5]),"+f"(d[6]),"+f"(d[7]),"+f"(d[8]),"+f"(d[9]),"+f"(d[10]),"+f"(d[11]),"+f"(d[12]),"+f"(d[13]),"+f"(d[14]),"+f"(d[15]),"+f"(d[16]),"+f"(d[17]),"+f"(d[18]),"+f"(d[19]),"+f"(d[20]),"+f"(d[21]),"+f"(d[22]),"+f"(d[23])
      : "l"(da), "l"(db), "r"(sd));
}
template<> __device__ __forceinline__ void mma_ssp<56>(float* d, uint64_t da, uint64_t db, int sd) {
    asm volatile("{\n.reg .pred p;\nsetp.ne.b32 p, %30, 0;\nwgmma.mma_async.sync.aligned.m64n56k16.f32.bf16.bf16 {%0,%1,%2,%3,%4,%5,%6,%7,%8,%9,%10,%11,%12,%13,%14,%15,%16,%17,%18,%19,%20,%21,%22,%23,%24,%25,%26,%27}, %28, %29, p, 1, 1, 0, 1;\n}\n"
      : "+f"(d[0]),"+f"(d[1]),"+f"(d[2]),"+f"(d[3]),"+f"(d[4]),"+f"(d[5]),"+f"(d[6]),"+f"(d[7]),"+f"(d[8]),"+f"(d[9]),"+f"(d[10]),"+f"(d[11]),"+f"(d[12]),"+f"(d[13]),"+f"(d[14]),"+f"(d[15]),"+f"(d[16]),"+f"(d[17]),"+f"(d[18]),"+f"(d[19]),"+f"(d[20]),"+f"(d[21]),"+f"(d[22]),"+f"(d[23]),"+f"(d[24]),"+f"(d[25]),"+f"(d[26]),"+f"(d[27])
      : "l"(da), "l"(db), "r"(sd));
}
template<> __device__ __forceinline__ void mma_ssp<64>(float* d, uint64_t da, uint64_t db, int sd) {
    asm volatile("{\n.reg .pred p;\nsetp.ne.b32 p, %34, 0;\nwgmma.mma_async.sync.aligned.m64n64k16.f32.bf16.bf16 {%0,%1,%2,%3,%4,%5,%6,%7,%8,%9,%10,%11,%12,%13,%14,%15,%16,%17,%18,%19,%20,%21,%22,%23,%24,%25,%26,%27,%28,%29,%30,%31}, %32, %33, p, 1, 1, 0, 1;\n}\n"
      : "+f"(d[0]),"+f"(d[1]),"+f"(d[2]),"+f"(d[3]),"+f"(d[4]),"+f"(d[5]),"+f"(d[6]),"+f"(d[7]),"+f"(d[8]),"+f"(d[9]),"+f"(d[10]),"+f"(d[11]),"+f"(d[12]),"+f"(d[13]),"+f"(d[14]),"+f"(d[15]),"+f"(d[16]),"+f"(d[17]),"+f"(d[18]),"+f"(d[19]),"+f"(d[20]),"+f"(d[21]),"+f"(d[22]),"+f"(d[23]),"+f"(d[24]),"+f"(d[25]),"+f"(d[26]),"+f"(d[27]),"+f"(d[28]),"+f"(d[29]),"+f"(d[30]),"+f"(d[31])
      : "l"(da), "l"(db), "r"(sd));
}
template<> __device__ __forceinline__ void mma_ssp<80>(float* d, uint64_t da, uint64_t db, int sd) {
    asm volatile("{\n.reg .pred p;\nsetp.ne.b32 p, %42, 0;\nwgmma.mma_async.sync.aligned.m64n80k16.f32.bf16.bf16 {%0,%1,%2,%3,%4,%5,%6,%7,%8,%9,%10,%11,%12,%13,%14,%15,%16,%17,%18,%19,%20,%21,%22,%23,%24,%25,%26,%27,%28,%29,%30,%31,%32,%33,%34,%35,%36,%37,%38,%39}, %40, %41, p, 1, 1, 0, 1;\n}\n"
      : "+f"(d[0]),"+f"(d[1]),"+f"(d[2]),"+f"(d[3]),"+f"(d[4]),"+f"(d[5]),"+f"(d[6]),"+f"(d[7]),"+f"(d[8]),"+f"(d[9]),"+f"(d[10]),"+f"(d[11]),"+f"(d[12]),"+f"(d[13]),"+f"(d[14]),"+f"(d[15]),"+f"(d[16]),"+f"(d[17]),"+f"(d[18]),"+f"(d[19]),"+f"(d[20]),"+f"(d[21]),"+f"(d[22]),"+f"(d[23]),"+f"(d[24]),"+f"(d[25]),"+f"(d[26]),"+f"(d[27]),"+f"(d[28]),"+f"(d[29]),"+f"(d[30]),"+f"(d[31]),"+f"(d[32]),"+f"(d[33]),"+f"(d[34]),"+f"(d[35]),"+f"(d[36]),"+f"(d[37]),"+f"(d[38]),"+f"(d[39])
      : "l"(da), "l"(db), "r"(sd));
}
template<> __device__ __forceinline__ void mma_ssp<128>(float* d, uint64_t da, uint64_t db, int sd) {
    asm volatile("{\n.reg .pred p;\nsetp.ne.b32 p, %66, 0;\nwgmma.mma_async.sync.aligned.m64n128k16.f32.bf16.bf16 {%0,%1,%2,%3,%4,%5,%6,%7,%8,%9,%10,%11,%12,%13,%14,%15,%16,%17,%18,%19,%20,%21,%22,%23,%24,%25,%26,%27,%28,%29,%30,%31,%32,%33,%34,%35,%36,%37,%38,%39,%40,%41,%42,%43,%44,%45,%46,%47,%48,%49,%50,%51,%52,%53,%54,%55,%56,%57,%58,%59,%60,%61,%62,%63}, %64, %65, p, 1, 1, 0, 1;\n}\n"
      : "+f"(d[0]),"+f"(d[1]),"+f"(d[2]),"+f"(d[3]),"+f"(d[4]),"+f"(d[5]),"+f"(d[6]),"+f"(d[7]),"+f"(d[8]),"+f"(d[9]),"+f"(d[10]),"+f"(d[11]),"+f"(d[12]),"+f"(d[13]),"+f"(d[14]),"+f"(d[15]),"+f"(d[16]),"+f"(d[17]),"+f"(d[18]),"+f"(d[19]),"+f"(d[20]),"+f"(d[21]),"+f"(d[22]),"+f"(d[23]),"+f"(d[24]),"+f"(d[25]),"+f"(d[26]),"+f"(d[27]),"+f"(d[28]),"+f"(d[29]),"+f"(d[30]),"+f"(d[31]),"+f"(d[32]),"+f"(d[33]),"+f"(d[34]),"+f"(d[35]),"+f"(d[36]),"+f"(d[37]),"+f"(d[38]),"+f"(d[39]),"+f"(d[40]),"+f"(d[41]),"+f"(d[42]),"+f"(d[43]),"+f"(d[44]),"+f"(d[45]),"+f"(d[46]),"+f"(d[47]),"+f"(d[48]),"+f"(d[49]),"+f"(d[50]),"+f"(d[51]),"+f"(d[52]),"+f"(d[53]),"+f"(d[54]),"+f"(d[55]),"+f"(d[56]),"+f"(d[57]),"+f"(d[58]),"+f"(d[59]),"+f"(d[60]),"+f"(d[61]),"+f"(d[62]),"+f"(d[63])
      : "l"(da), "l"(db), "r"(sd));
}
template<> __device__ __forceinline__ void mma_ssp<152>(float* d, uint64_t da, uint64_t db, int sd) {
    asm volatile("{\n.reg .pred p;\nsetp.ne.b32 p, %78, 0;\nwgmma.mma_async.sync.aligned.m64n152k16.f32.bf16.bf16 {%0,%1,%2,%3,%4,%5,%6,%7,%8,%9,%10,%11,%12,%13,%14,%15,%16,%17,%18,%19,%20,%21,%22,%23,%24,%25,%26,%27,%28,%29,%30,%31,%32,%33,%34,%35,%36,%37,%38,%39,%40,%41,%42,%43,%44,%45,%46,%47,%48,%49,%50,%51,%52,%53,%54,%55,%56,%57,%58,%59,%60,%61,%62,%63,%64,%65,%66,%67,%68,%69,%70,%71,%72,%73,%74,%75}, %76, %77, p, 1, 1, 0, 1;\n}\n"
      : "+f"(d[0]),"+f"(d[1]),"+f"(d[2]),"+f"(d[3]),"+f"(d[4]),"+f"(d[5]),"+f"(d[6]),"+f"(d[7]),"+f"(d[8]),"+f"(d[9]),"+f"(d[10]),"+f"(d[11]),"+f"(d[12]),"+f"(d[13]),"+f"(d[14]),"+f"(d[15]),"+f"(d[16]),"+f"(d[17]),"+f"(d[18]),"+f"(d[19]),"+f"(d[20]),"+f"(d[21]),"+f"(d[22]),"+f"(d[23]),"+f"(d[24]),"+f"(d[25]),"+f"(d[26]),"+f"(d[27]),"+f"(d[28]),"+f"(d[29]),"+f"(d[30]),"+f"(d[31]),"+f"(d[32]),"+f"(d[33]),"+f"(d[34]),"+f"(d[35]),"+f"(d[36]),"+f"(d[37]),"+f"(d[38]),"+f"(d[39]),"+f"(d[40]),"+f"(d[41]),"+f"(d[42]),"+f"(d[43]),"+f"(d[44]),"+f"(d[45]),"+f"(d[46]),"+f"(d[47]),"+f"(d[48]),"+f"(d[49]),"+f"(d[50]),"+f"(d[51]),"+f"(d[52]),"+f"(d[53]),"+f"(d[54]),"+f"(d[55]),"+f"(d[56]),"+f"(d[57]),"+f"(d[58]),"+f"(d[59]),"+f"(d[60]),"+f"(d[61]),"+f"(d[62]),"+f"(d[63]),"+f"(d[64]),"+f"(d[65]),"+f"(d[66]),"+f"(d[67]),"+f"(d[68]),"+f"(d[69]),"+f"(d[70]),"+f"(d[71]),"+f"(d[72]),"+f"(d[73]),"+f"(d[74]),"+f"(d[75])
      : "l"(da), "l"(db), "r"(sd));
}
template<> __device__ __forceinline__ void mma_ssp<160>(float* d, uint64_t da, uint64_t db, int sd) {
    asm volatile("{\n.reg .pred p;\nsetp.ne.b32 p, %82, 0;\nwgmma.mma_async.sync.aligned.m64n160k16.f32.bf16.bf16 {%0,%1,%2,%3,%4,%5,%6,%7,%8,%9,%10,%11,%12,%13,%14,%15,%16,%17,%18,%19,%20,%21,%22,%23,%24,%25,%26,%27,%28,%29,%30,%31,%32,%33,%34,%35,%36,%37,%38,%39,%40,%41,%42,%43,%44,%45,%46,%47,%48,%49,%50,%51,%52,%53,%54,%55,%56,%57,%58,%59,%60,%61,%62,%63,%64,%65,%66,%67,%68,%69,%70,%71,%72,%73,%74,%75,%76,%77,%78,%79}, %80, %81, p, 1, 1, 0, 1;\n}\n"
      : "+f"(d[0]),"+f"(d[1]),"+f"(d[2]),"+f"(d[3]),"+f"(d[4]),"+f"(d[5]),"+f"(d[6]),"+f"(d[7]),"+f"(d[8]),"+f"(d[9]),"+f"(d[10]),"+f"(d[11]),"+f"(d[12]),"+f"(d[13]),"+f"(d[14]),"+f"(d[15]),"+f"(d[16]),"+f"(d[17]),"+f"(d[18]),"+f"(d[19]),"+f"(d[20]),"+f"(d[21]),"+f"(d[22]),"+f"(d[23]),"+f"(d[24]),"+f"(d[25]),"+f"(d[26]),"+f"(d[27]),"+f"(d[28]),"+f"(d[29]),"+f"(d[30]),"+f"(d[31]),"+f"(d[32]),"+f"(d[33]),"+f"(d[34]),"+f"(d[35]),"+f"(d[36]),"+f"(d[37]),"+f"(d[38]),"+f"(d[39]),"+f"(d[40]),"+f"(d[41]),"+f"(d[42]),"+f"(d[43]),"+f"(d[44]),"+f"(d[45]),"+f"(d[46]),"+f"(d[47]),"+f"(d[48]),"+f"(d[49]),"+f"(d[50]),"+f"(d[51]),"+f"(d[52]),"+f"(d[53]),"+f"(d[54]),"+f"(d[55]),"+f"(d[56]),"+f"(d[57]),"+f"(d[58]),"+f"(d[59]),"+f"(d[60]),"+f"(d[61]),"+f"(d[62]),"+f"(d[63]),"+f"(d[64]),"+f"(d[65]),"+f"(d[66]),"+f"(d[67]),"+f"(d[68]),"+f"(d[69]),"+f"(d[70]),"+f"(d[71]),"+f"(d[72]),"+f"(d[73]),"+f"(d[74]),"+f"(d[75]),"+f"(d[76]),"+f"(d[77]),"+f"(d[78]),"+f"(d[79])
      : "l"(da), "l"(db), "r"(sd));
}
template<> __device__ __forceinline__ void mma_ssp<168>(float* d, uint64_t da, uint64_t db, int sd) {
    asm volatile("{\n.reg .pred p;\nsetp.ne.b32 p, %86, 0;\nwgmma.mma_async.sync.aligned.m64n168k16.f32.bf16.bf16 {%0,%1,%2,%3,%4,%5,%6,%7,%8,%9,%10,%11,%12,%13,%14,%15,%16,%17,%18,%19,%20,%21,%22,%23,%24,%25,%26,%27,%28,%29,%30,%31,%32,%33,%34,%35,%36,%37,%38,%39,%40,%41,%42,%43,%44,%45,%46,%47,%48,%49,%50,%51,%52,%53,%54,%55,%56,%57,%58,%59,%60,%61,%62,%63,%64,%65,%66,%67,%68,%69,%70,%71,%72,%73,%74,%75,%76,%77,%78,%79,%80,%81,%82,%83}, %84, %85, p, 1, 1, 0, 1;\n}\n"
      : "+f"(d[0]),"+f"(d[1]),"+f"(d[2]),"+f"(d[3]),"+f"(d[4]),"+f"(d[5]),"+f"(d[6]),"+f"(d[7]),"+f"(d[8]),"+f"(d[9]),"+f"(d[10]),"+f"(d[11]),"+f"(d[12]),"+f"(d[13]),"+f"(d[14]),"+f"(d[15]),"+f"(d[16]),"+f"(d[17]),"+f"(d[18]),"+f"(d[19]),"+f"(d[20]),"+f"(d[21]),"+f"(d[22]),"+f"(d[23]),"+f"(d[24]),"+f"(d[25]),"+f"(d[26]),"+f"(d[27]),"+f"(d[28]),"+f"(d[29]),"+f"(d[30]),"+f"(d[31]),"+f"(d[32]),"+f"(d[33]),"+f"(d[34]),"+f"(d[35]),"+f"(d[36]),"+f"(d[37]),"+f"(d[38]),"+f"(d[39]),"+f"(d[40]),"+f"(d[41]),"+f"(d[42]),"+f"(d[43]),"+f"(d[44]),"+f"(d[45]),"+f"(d[46]),"+f"(d[47]),"+f"(d[48]),"+f"(d[49]),"+f"(d[50]),"+f"(d[51]),"+f"(d[52]),"+f"(d[53]),"+f"(d[54]),"+f"(d[55]),"+f"(d[56]),"+f"(d[57]),"+f"(d[58]),"+f"(d[59]),"+f"(d[60]),"+f"(d[61]),"+f"(d[62]),"+f"(d[63]),"+f"(d[64]),"+f"(d[65]),"+f"(d[66]),"+f"(d[67]),"+f"(d[68]),"+f"(d[69]),"+f"(d[70]),"+f"(d[71]),"+f"(d[72]),"+f"(d[73]),"+f"(d[74]),"+f"(d[75]),"+f"(d[76]),"+f"(d[77]),"+f"(d[78]),"+f"(d[79]),"+f"(d[80]),"+f"(d[81]),"+f"(d[82]),"+f"(d[83])
      : "l"(da), "l"(db), "r"(sd));
}
template<> __device__ __forceinline__ void mma_ssp<176>(float* d, uint64_t da, uint64_t db, int sd) {
    asm volatile("{\n.reg .pred p;\nsetp.ne.b32 p, %90, 0;\nwgmma.mma_async.sync.aligned.m64n176k16.f32.bf16.bf16 {%0,%1,%2,%3,%4,%5,%6,%7,%8,%9,%10,%11,%12,%13,%14,%15,%16,%17,%18,%19,%20,%21,%22,%23,%24,%25,%26,%27,%28,%29,%30,%31,%32,%33,%34,%35,%36,%37,%38,%39,%40,%41,%42,%43,%44,%45,%46,%47,%48,%49,%50,%51,%52,%53,%54,%55,%56,%57,%58,%59,%60,%61,%62,%63,%64,%65,%66,%67,%68,%69,%70,%71,%72,%73,%74,%75,%76,%77,%78,%79,%80,%81,%82,%83,%84,%85,%86,%87}, %88, %89, p, 1, 1, 0, 1;\n}\n"
      : "+f"(d[0]),"+f"(d[1]),"+f"(d[2]),"+f"(d[3]),"+f"(d[4]),"+f"(d[5]),"+f"(d[6]),"+f"(d[7]),"+f"(d[8]),"+f"(d[9]),"+f"(d[10]),"+f"(d[11]),"+f"(d[12]),"+f"(d[13]),"+f"(d[14]),"+f"(d[15]),"+f"(d[16]),"+f"(d[17]),"+f"(d[18]),"+f"(d[19]),"+f"(d[20]),"+f"(d[21]),"+f"(d[22]),"+f"(d[23]),"+f"(d[24]),"+f"(d[25]),"+f"(d[26]),"+f"(d[27]),"+f"(d[28]),"+f"(d[29]),"+f"(d[30]),"+f"(d[31]),"+f"(d[32]),"+f"(d[33]),"+f"(d[34]),"+f"(d[35]),"+f"(d[36]),"+f"(d[37]),"+f"(d[38]),"+f"(d[39]),"+f"(d[40]),"+f"(d[41]),"+f"(d[42]),"+f"(d[43]),"+f"(d[44]),"+f"(d[45]),"+f"(d[46]),"+f"(d[47]),"+f"(d[48]),"+f"(d[49]),"+f"(d[50]),"+f"(d[51]),"+f"(d[52]),"+f"(d[53]),"+f"(d[54]),"+f"(d[55]),"+f"(d[56]),"+f"(d[57]),"+f"(d[58]),"+f"(d[59]),"+f"(d[60]),"+f"(d[61]),"+f"(d[62]),"+f"(d[63]),"+f"(d[64]),"+f"(d[65]),"+f"(d[66]),"+f"(d[67]),"+f"(d[68]),"+f"(d[69]),"+f"(d[70]),"+f"(d[71]),"+f"(d[72]),"+f"(d[73]),"+f"(d[74]),"+f"(d[75]),"+f"(d[76]),"+f"(d[77]),"+f"(d[78]),"+f"(d[79]),"+f"(d[80]),"+f"(d[81]),"+f"(d[82]),"+f"(d[83]),"+f"(d[84]),"+f"(d[85]),"+f"(d[86]),"+f"(d[87])
      : "l"(da), "l"(db), "r"(sd));
}
template<> __device__ __forceinline__ void mma_ssp<184>(float* d, uint64_t da, uint64_t db, int sd) {
    asm volatile("{\n.reg .pred p;\nsetp.ne.b32 p, %94, 0;\nwgmma.mma_async.sync.aligned.m64n184k16.f32.bf16.bf16 {%0,%1,%2,%3,%4,%5,%6,%7,%8,%9,%10,%11,%12,%13,%14,%15,%16,%17,%18,%19,%20,%21,%22,%23,%24,%25,%26,%27,%28,%29,%30,%31,%32,%33,%34,%35,%36,%37,%38,%39,%40,%41,%42,%43,%44,%45,%46,%47,%48,%49,%50,%51,%52,%53,%54,%55,%56,%57,%58,%59,%60,%61,%62,%63,%64,%65,%66,%67,%68,%69,%70,%71,%72,%73,%74,%75,%76,%77,%78,%79,%80,%81,%82,%83,%84,%85,%86,%87,%88,%89,%90,%91}, %92, %93, p, 1, 1, 0, 1;\n}\n"
      : "+f"(d[0]),"+f"(d[1]),"+f"(d[2]),"+f"(d[3]),"+f"(d[4]),"+f"(d[5]),"+f"(d[6]),"+f"(d[7]),"+f"(d[8]),"+f"(d[9]),"+f"(d[10]),"+f"(d[11]),"+f"(d[12]),"+f"(d[13]),"+f"(d[14]),"+f"(d[15]),"+f"(d[16]),"+f"(d[17]),"+f"(d[18]),"+f"(d[19]),"+f"(d[20]),"+f"(d[21]),"+f"(d[22]),"+f"(d[23]),"+f"(d[24]),"+f"(d[25]),"+f"(d[26]),"+f"(d[27]),"+f"(d[28]),"+f"(d[29]),"+f"(d[30]),"+f"(d[31]),"+f"(d[32]),"+f"(d[33]),"+f"(d[34]),"+f"(d[35]),"+f"(d[36]),"+f"(d[37]),"+f"(d[38]),"+f"(d[39]),"+f"(d[40]),"+f"(d[41]),"+f"(d[42]),"+f"(d[43]),"+f"(d[44]),"+f"(d[45]),"+f"(d[46]),"+f"(d[47]),"+f"(d[48]),"+f"(d[49]),"+f"(d[50]),"+f"(d[51]),"+f"(d[52]),"+f"(d[53]),"+f"(d[54]),"+f"(d[55]),"+f"(d[56]),"+f"(d[57]),"+f"(d[58]),"+f"(d[59]),"+f"(d[60]),"+f"(d[61]),"+f"(d[62]),"+f"(d[63]),"+f"(d[64]),"+f"(d[65]),"+f"(d[66]),"+f"(d[67]),"+f"(d[68]),"+f"(d[69]),"+f"(d[70]),"+f"(d[71]),"+f"(d[72]),"+f"(d[73]),"+f"(d[74]),"+f"(d[75]),"+f"(d[76]),"+f"(d[77]),"+f"(d[78]),"+f"(d[79]),"+f"(d[80]),"+f"(d[81]),"+f"(d[82]),"+f"(d[83]),"+f"(d[84]),"+f"(d[85]),"+f"(d[86]),"+f"(d[87]),"+f"(d[88]),"+f"(d[89]),"+f"(d[90]),"+f"(d[91])
      : "l"(da), "l"(db), "r"(sd));
}
template<> __device__ __forceinline__ void mma_ssp<192>(float* d, uint64_t da, uint64_t db, int sd) {
    asm volatile("{\n.reg .pred p;\nsetp.ne.b32 p, %98, 0;\nwgmma.mma_async.sync.aligned.m64n192k16.f32.bf16.bf16 {%0,%1,%2,%3,%4,%5,%6,%7,%8,%9,%10,%11,%12,%13,%14,%15,%16,%17,%18,%19,%20,%21,%22,%23,%24,%25,%26,%27,%28,%29,%30,%31,%32,%33,%34,%35,%36,%37,%38,%39,%40,%41,%42,%43,%44,%45,%46,%47,%48,%49,%50,%51,%52,%53,%54,%55,%56,%57,%58,%59,%60,%61,%62,%63,%64,%65,%66,%67,%68,%69,%70,%71,%72,%73,%74,%75,%76,%77,%78,%79,%80,%81,%82,%83,%84,%85,%86,%87,%88,%89,%90,%91,%92,%93,%94,%95}, %96, %97, p, 1, 1, 0, 1;\n}\n"
      : "+f"(d[0]),"+f"(d[1]),"+f"(d[2]),"+f"(d[3]),"+f"(d[4]),"+f"(d[5]),"+f"(d[6]),"+f"(d[7]),"+f"(d[8]),"+f"(d[9]),"+f"(d[10]),"+f"(d[11]),"+f"(d[12]),"+f"(d[13]),"+f"(d[14]),"+f"(d[15]),"+f"(d[16]),"+f"(d[17]),"+f"(d[18]),"+f"(d[19]),"+f"(d[20]),"+f"(d[21]),"+f"(d[22]),"+f"(d[23]),"+f"(d[24]),"+f"(d[25]),"+f"(d[26]),"+f"(d[27]),"+f"(d[28]),"+f"(d[29]),"+f"(d[30]),"+f"(d[31]),"+f"(d[32]),"+f"(d[33]),"+f"(d[34]),"+f"(d[35]),"+f"(d[36]),"+f"(d[37]),"+f"(d[38]),"+f"(d[39]),"+f"(d[40]),"+f"(d[41]),"+f"(d[42]),"+f"(d[43]),"+f"(d[44]),"+f"(d[45]),"+f"(d[46]),"+f"(d[47]),"+f"(d[48]),"+f"(d[49]),"+f"(d[50]),"+f"(d[51]),"+f"(d[52]),"+f"(d[53]),"+f"(d[54]),"+f"(d[55]),"+f"(d[56]),"+f"(d[57]),"+f"(d[58]),"+f"(d[59]),"+f"(d[60]),"+f"(d[61]),"+f"(d[62]),"+f"(d[63]),"+f"(d[64]),"+f"(d[65]),"+f"(d[66]),"+f"(d[67]),"+f"(d[68]),"+f"(d[69]),"+f"(d[70]),"+f"(d[71]),"+f"(d[72]),"+f"(d[73]),"+f"(d[74]),"+f"(d[75]),"+f"(d[76]),"+f"(d[77]),"+f"(d[78]),"+f"(d[79]),"+f"(d[80]),"+f"(d[81]),"+f"(d[82]),"+f"(d[83]),"+f"(d[84]),"+f"(d[85]),"+f"(d[86]),"+f"(d[87]),"+f"(d[88]),"+f"(d[89]),"+f"(d[90]),"+f"(d[91]),"+f"(d[92]),"+f"(d[93]),"+f"(d[94]),"+f"(d[95])
      : "l"(da), "l"(db), "r"(sd));
}
template<> __device__ __forceinline__ void mma_ssp<200>(float* d, uint64_t da, uint64_t db, int sd) {
    asm volatile("{\n.reg .pred p;\nsetp.ne.b32 p, %102, 0;\nwgmma.mma_async.sync.aligned.m64n200k16.f32.bf16.bf16 {%0,%1,%2,%3,%4,%5,%6,%7,%8,%9,%10,%11,%12,%13,%14,%15,%16,%17,%18,%19,%20,%21,%22,%23,%24,%25,%26,%27,%28,%29,%30,%31,%32,%33,%34,%35,%36,%37,%38,%39,%40,%41,%42,%43,%44,%45,%46,%47,%48,%49,%50,%51,%52,%53,%54,%55,%56,%57,%58,%59,%60,%61,%62,%63,%64,%65,%66,%67,%68,%69,%70,%71,%72,%73,%74,%75,%76,%77,%78,%79,%80,%81,%82,%83,%84,%85,%86,%87,%88,%89,%90,%91,%92,%93,%94,%95,%96,%97,%98,%99}, %100, %101, p, 1, 1, 0, 1;\n}\n"
      : "+f"(d[0]),"+f"(d[1]),"+f"(d[2]),"+f"(d[3]),"+f"(d[4]),"+f"(d[5]),"+f"(d[6]),"+f"(d[7]),"+f"(d[8]),"+f"(d[9]),"+f"(d[10]),"+f"(d[11]),"+f"(d[12]),"+f"(d[13]),"+f"(d[14]),"+f"(d[15]),"+f"(d[16]),"+f"(d[17]),"+f"(d[18]),"+f"(d[19]),"+f"(d[20]),"+f"(d[21]),"+f"(d[22]),"+f"(d[23]),"+f"(d[24]),"+f"(d[25]),"+f"(d[26]),"+f"(d[27]),"+f"(d[28]),"+f"(d[29]),"+f"(d[30]),"+f"(d[31]),"+f"(d[32]),"+f"(d[33]),"+f"(d[34]),"+f"(d[35]),"+f"(d[36]),"+f"(d[37]),"+f"(d[38]),"+f"(d[39]),"+f"(d[40]),"+f"(d[41]),"+f"(d[42]),"+f"(d[43]),"+f"(d[44]),"+f"(d[45]),"+f"(d[46]),"+f"(d[47]),"+f"(d[48]),"+f"(d[49]),"+f"(d[50]),"+f"(d[51]),"+f"(d[52]),"+f"(d[53]),"+f"(d[54]),"+f"(d[55]),"+f"(d[56]),"+f"(d[57]),"+f"(d[58]),"+f"(d[59]),"+f"(d[60]),"+f"(d[61]),"+f"(d[62]),"+f"(d[63]),"+f"(d[64]),"+f"(d[65]),"+f"(d[66]),"+f"(d[67]),"+f"(d[68]),"+f"(d[69]),"+f"(d[70]),"+f"(d[71]),"+f"(d[72]),"+f"(d[73]),"+f"(d[74]),"+f"(d[75]),"+f"(d[76]),"+f"(d[77]),"+f"(d[78]),"+f"(d[79]),"+f"(d[80]),"+f"(d[81]),"+f"(d[82]),"+f"(d[83]),"+f"(d[84]),"+f"(d[85]),"+f"(d[86]),"+f"(d[87]),"+f"(d[88]),"+f"(d[89]),"+f"(d[90]),"+f"(d[91]),"+f"(d[92]),"+f"(d[93]),"+f"(d[94]),"+f"(d[95]),"+f"(d[96]),"+f"(d[97]),"+f"(d[98]),"+f"(d[99])
      : "l"(da), "l"(db), "r"(sd));
}
template<int SD> __device__ __forceinline__ void mma_n192_ss(float* d, uint64_t da, uint64_t db) {
    asm volatile("wgmma.mma_async.sync.aligned.m64n192k16.f32.bf16.bf16 {%0,%1,%2,%3,%4,%5,%6,%7,%8,%9,%10,%11,%12,%13,%14,%15,%16,%17,%18,%19,%20,%21,%22,%23,%24,%25,%26,%27,%28,%29,%30,%31,%32,%33,%34,%35,%36,%37,%38,%39,%40,%41,%42,%43,%44,%45,%46,%47,%48,%49,%50,%51,%52,%53,%54,%55,%56,%57,%58,%59,%60,%61,%62,%63,%64,%65,%66,%67,%68,%69,%70,%71,%72,%73,%74,%75,%76,%77,%78,%79,%80,%81,%82,%83,%84,%85,%86,%87,%88,%89,%90,%91,%92,%93,%94,%95}, %96, %97, %98, 1, 1, 0, 1;\n"
      : "+f"(d[0]),"+f"(d[1]),"+f"(d[2]),"+f"(d[3]),"+f"(d[4]),"+f"(d[5]),"+f"(d[6]),"+f"(d[7]),"+f"(d[8]),"+f"(d[9]),"+f"(d[10]),"+f"(d[11]),"+f"(d[12]),"+f"(d[13]),"+f"(d[14]),"+f"(d[15]),"+f"(d[16]),"+f"(d[17]),"+f"(d[18]),"+f"(d[19]),"+f"(d[20]),"+f"(d[21]),"+f"(d[22]),"+f"(d[23]),"+f"(d[24]),"+f"(d[25]),"+f"(d[26]),"+f"(d[27]),"+f"(d[28]),"+f"(d[29]),"+f"(d[30]),"+f"(d[31]),"+f"(d[32]),"+f"(d[33]),"+f"(d[34]),"+f"(d[35]),"+f"(d[36]),"+f"(d[37]),"+f"(d[38]),"+f"(d[39]),"+f"(d[40]),"+f"(d[41]),"+f"(d[42]),"+f"(d[43]),"+f"(d[44]),"+f"(d[45]),"+f"(d[46]),"+f"(d[47]),"+f"(d[48]),"+f"(d[49]),"+f"(d[50]),"+f"(d[51]),"+f"(d[52]),"+f"(d[53]),"+f"(d[54]),"+f"(d[55]),"+f"(d[56]),"+f"(d[57]),"+f"(d[58]),"+f"(d[59]),"+f"(d[60]),"+f"(d[61]),"+f"(d[62]),"+f"(d[63]),"+f"(d[64]),"+f"(d[65]),"+f"(d[66]),"+f"(d[67]),"+f"(d[68]),"+f"(d[69]),"+f"(d[70]),"+f"(d[71]),"+f"(d[72]),"+f"(d[73]),"+f"(d[74]),"+f"(d[75]),"+f"(d[76]),"+f"(d[77]),"+f"(d[78]),"+f"(d[79]),"+f"(d[80]),"+f"(d[81]),"+f"(d[82]),"+f"(d[83]),"+f"(d[84]),"+f"(d[85]),"+f"(d[86]),"+f"(d[87]),"+f"(d[88]),"+f"(d[89]),"+f"(d[90]),"+f"(d[91]),"+f"(d[92]),"+f"(d[93]),"+f"(d[94]),"+f"(d[95])
      : "l"(da), "l"(db), "n"(SD));
}
template<int SD> __device__ __forceinline__ void mma_n64_ss(float* d, uint64_t da, uint64_t db) {
    asm volatile("wgmma.mma_async.sync.aligned.m64n64k16.f32.bf16.bf16 {%0,%1,%2,%3,%4,%5,%6,%7,%8,%9,%10,%11,%12,%13,%14,%15,%16,%17,%18,%19,%20,%21,%22,%23,%24,%25,%26,%27,%28,%29,%30,%31}, %32, %33, %34, 1, 1, 0, 1;\n"
      : "+f"(d[0]),"+f"(d[1]),"+f"(d[2]),"+f"(d[3]),"+f"(d[4]),"+f"(d[5]),"+f"(d[6]),"+f"(d[7]),"+f"(d[8]),"+f"(d[9]),"+f"(d[10]),"+f"(d[11]),"+f"(d[12]),"+f"(d[13]),"+f"(d[14]),"+f"(d[15]),"+f"(d[16]),"+f"(d[17]),"+f"(d[18]),"+f"(d[19]),"+f"(d[20]),"+f"(d[21]),"+f"(d[22]),"+f"(d[23]),"+f"(d[24]),"+f"(d[25]),"+f"(d[26]),"+f"(d[27]),"+f"(d[28]),"+f"(d[29]),"+f"(d[30]),"+f"(d[31])
      : "l"(da), "l"(db), "n"(SD));
}
template<int SD> __device__ __forceinline__ void mma_n128_ss(float* d, uint64_t da, uint64_t db) {
    asm volatile("wgmma.mma_async.sync.aligned.m64n128k16.f32.bf16.bf16 {%0,%1,%2,%3,%4,%5,%6,%7,%8,%9,%10,%11,%12,%13,%14,%15,%16,%17,%18,%19,%20,%21,%22,%23,%24,%25,%26,%27,%28,%29,%30,%31,%32,%33,%34,%35,%36,%37,%38,%39,%40,%41,%42,%43,%44,%45,%46,%47,%48,%49,%50,%51,%52,%53,%54,%55,%56,%57,%58,%59,%60,%61,%62,%63}, %64, %65, %66, 1, 1, 0, 1;\n"
      : "+f"(d[0]),"+f"(d[1]),"+f"(d[2]),"+f"(d[3]),"+f"(d[4]),"+f"(d[5]),"+f"(d[6]),"+f"(d[7]),"+f"(d[8]),"+f"(d[9]),"+f"(d[10]),"+f"(d[11]),"+f"(d[12]),"+f"(d[13]),"+f"(d[14]),"+f"(d[15]),"+f"(d[16]),"+f"(d[17]),"+f"(d[18]),"+f"(d[19]),"+f"(d[20]),"+f"(d[21]),"+f"(d[22]),"+f"(d[23]),"+f"(d[24]),"+f"(d[25]),"+f"(d[26]),"+f"(d[27]),"+f"(d[28]),"+f"(d[29]),"+f"(d[30]),"+f"(d[31]),"+f"(d[32]),"+f"(d[33]),"+f"(d[34]),"+f"(d[35]),"+f"(d[36]),"+f"(d[37]),"+f"(d[38]),"+f"(d[39]),"+f"(d[40]),"+f"(d[41]),"+f"(d[42]),"+f"(d[43]),"+f"(d[44]),"+f"(d[45]),"+f"(d[46]),"+f"(d[47]),"+f"(d[48]),"+f"(d[49]),"+f"(d[50]),"+f"(d[51]),"+f"(d[52]),"+f"(d[53]),"+f"(d[54]),"+f"(d[55]),"+f"(d[56]),"+f"(d[57]),"+f"(d[58]),"+f"(d[59]),"+f"(d[60]),"+f"(d[61]),"+f"(d[62]),"+f"(d[63])
      : "l"(da), "l"(db), "n"(SD));
}
template<int SD> __device__ __forceinline__ void mma_n64_rs(float* d, uint32_t a0, uint32_t a1, uint32_t a2, uint32_t a3, uint64_t db) {
    asm volatile("wgmma.mma_async.sync.aligned.m64n64k16.f32.bf16.bf16 {%0,%1,%2,%3,%4,%5,%6,%7,%8,%9,%10,%11,%12,%13,%14,%15,%16,%17,%18,%19,%20,%21,%22,%23,%24,%25,%26,%27,%28,%29,%30,%31}, {%32,%33,%34,%35}, %36, %37, 1, 1, 0;\n"
      : "+f"(d[0]),"+f"(d[1]),"+f"(d[2]),"+f"(d[3]),"+f"(d[4]),"+f"(d[5]),"+f"(d[6]),"+f"(d[7]),"+f"(d[8]),"+f"(d[9]),"+f"(d[10]),"+f"(d[11]),"+f"(d[12]),"+f"(d[13]),"+f"(d[14]),"+f"(d[15]),"+f"(d[16]),"+f"(d[17]),"+f"(d[18]),"+f"(d[19]),"+f"(d[20]),"+f"(d[21]),"+f"(d[22]),"+f"(d[23]),"+f"(d[24]),"+f"(d[25]),"+f"(d[26]),"+f"(d[27]),"+f"(d[28]),"+f"(d[29]),"+f"(d[30]),"+f"(d[31])
      : "r"(a0), "r"(a1), "r"(a2), "r"(a3), "l"(db), "n"(SD));
}
template<int SD> __device__ __forceinline__ void mma_n64_sk(float* d, uint64_t da, uint64_t db) {
    asm volatile("wgmma.mma_async.sync.aligned.m64n64k16.f32.bf16.bf16 {%0,%1,%2,%3,%4,%5,%6,%7,%8,%9,%10,%11,%12,%13,%14,%15,%16,%17,%18,%19,%20,%21,%22,%23,%24,%25,%26,%27,%28,%29,%30,%31}, %32, %33, %34, 1, 1, 0, 0;\n"
      : "+f"(d[0]),"+f"(d[1]),"+f"(d[2]),"+f"(d[3]),"+f"(d[4]),"+f"(d[5]),"+f"(d[6]),"+f"(d[7]),"+f"(d[8]),"+f"(d[9]),"+f"(d[10]),"+f"(d[11]),"+f"(d[12]),"+f"(d[13]),"+f"(d[14]),"+f"(d[15]),"+f"(d[16]),"+f"(d[17]),"+f"(d[18]),"+f"(d[19]),"+f"(d[20]),"+f"(d[21]),"+f"(d[22]),"+f"(d[23]),"+f"(d[24]),"+f"(d[25]),"+f"(d[26]),"+f"(d[27]),"+f"(d[28]),"+f"(d[29]),"+f"(d[30]),"+f"(d[31])
      : "l"(da), "l"(db), "n"(SD));
}
template<int SD> __device__ __forceinline__ void mma_n24_rs(float* d, uint32_t a0, uint32_t a1, uint32_t a2, uint32_t a3, uint64_t db) {
    asm volatile("wgmma.mma_async.sync.aligned.m64n24k16.f32.bf16.bf16 {%0,%1,%2,%3,%4,%5,%6,%7,%8,%9,%10,%11}, {%12,%13,%14,%15}, %16, %17, 1, 1, 1;\n"
      : "+f"(d[0]),"+f"(d[1]),"+f"(d[2]),"+f"(d[3]),"+f"(d[4]),"+f"(d[5]),"+f"(d[6]),"+f"(d[7]),"+f"(d[8]),"+f"(d[9]),"+f"(d[10]),"+f"(d[11])
      : "r"(a0), "r"(a1), "r"(a2), "r"(a3), "l"(db), "n"(SD));
}

__host__ __device__ constexpr uint64_t mkdesc(uint32_t addr, uint32_t lbo, uint32_t sbo, uint32_t swz) {
    return (uint64_t)((addr & 0x3FFFF) >> 4) | ((uint64_t)(lbo >> 4) << 16) | ((uint64_t)(sbo >> 4) << 32) | ((uint64_t)swz << 62);
}
#define WG_FENCE() asm volatile("wgmma.fence.sync.aligned;" ::: "memory")
#define WG_COMMIT() asm volatile("wgmma.commit_group.sync.aligned;" ::: "memory")
#define WG_WAIT(n) asm volatile("wgmma.wait_group.sync.aligned " #n ";" ::: "memory")
template<int N> __device__ __forceinline__ void keep(float* r) {
#pragma unroll
    for (int i = 0; i < N; i++) asm volatile("" : "+f"(r[i]) :: "memory");
}
template<int N> __device__ __forceinline__ void kill(float* r) {
#pragma unroll
    for (int i = 0; i < N; i++) asm volatile("" : "=f"(r[i]));
}
template<int N> __device__ __forceinline__ void keep(uint32_t* r) {
#pragma unroll
    for (int i = 0; i < N; i++) asm volatile("" : "+r"(r[i]) :: "memory");
}
__device__ __forceinline__ uint32_t cl(uint32_t a) { return a + ((blockIdx.x & 1) << 24); }
__device__ __forceinline__ void mbar_init(uint32_t a, uint32_t c) { asm volatile("mbarrier.init.shared::cta.b64 [%0], %1;" :: "r"(cl(a)), "r"(c) : "memory"); }
__device__ __forceinline__ void mbar_arrive(uint32_t a) { asm volatile("mbarrier.arrive.shared::cta.b64 _, [%0];" :: "r"(cl(a)) : "memory"); }
__device__ __forceinline__ void mbar_wait(uint32_t a, uint32_t ph) {
    asm volatile("{\n.reg .pred p, q;\n.reg .u32 n;\nmov.u32 n, 0;\n"
        "LW:\nmbarrier.try_wait.parity.shared::cta.b64 p, [%0], %1;\n@p bra LD;\n"
        "add.u32 n, n, 1;\nsetp.gt.u32 q, n, 2000000;\n@q trap;\nbra LW;\nLD:\n}" :: "r"(cl(a)), "r"(ph) : "memory");
}
__device__ __forceinline__ void mbar_wait_raw(uint32_t addr, uint32_t ph) {
    asm volatile("{\n.reg .pred p, q;\n.reg .u32 n;\nmbarrier.try_wait.parity.shared::cta.b64 p, [%0], %1;\n@p bra LD;\nmov.u32 n, 0;\n"
        "LW:\nmbarrier.try_wait.parity.shared::cta.b64 p, [%0], %1;\n@p bra LD;\n"
        "add.u32 n, n, 1;\nsetp.gt.u32 q, n, 2000000;\n@q trap;\nbra LW;\nLD:\n}" :: "r"(addr), "r"(ph) : "memory");
}
__device__ __forceinline__ void flag_wait(const unsigned* p, unsigned target) {
    asm volatile("{\n.reg .pred p, q;\n.reg .u32 n, v;\nmov.u32 n, 0;\n"
        "LW:\nld.acquire.gpu.global.u32 v, [%0];\nsub.u32 v, v, %1;\nsetp.ge.s32 p, v, 0;\n@p bra LD;\n"
        "nanosleep.u32 100;\nadd.u32 n, n, 1;\nsetp.gt.u32 q, n, 4000000;\n@q trap;\nbra LW;\nLD:\n}" :: "l"(p), "r"(target) : "memory");
}
__device__ __forceinline__ void red_release(unsigned* p, unsigned v) { asm volatile("red.release.gpu.global.add.u32 [%0], %1;" :: "l"(p), "r"(v) : "memory"); }
__device__ __forceinline__ void red_relaxed(unsigned* p, unsigned v) { asm volatile("red.relaxed.gpu.global.add.u32 [%0], %1;" :: "l"(p), "r"(v) : "memory"); }
__device__ __forceinline__ void st_release(unsigned* p, unsigned v) { asm volatile("st.release.gpu.global.u32 [%0], %1;" :: "l"(p), "r"(v) : "memory"); }
__device__ __forceinline__ unsigned ld_relaxed(const unsigned* p) { unsigned v; asm volatile("ld.relaxed.gpu.global.u32 %0, [%1];" : "=r"(v) : "l"(p) : "memory"); return v; }
__device__ __forceinline__ unsigned ld_acquire(const unsigned* p) { unsigned v; asm volatile("ld.acquire.gpu.global.u32 %0, [%1];" : "=r"(v) : "l"(p) : "memory"); return v; }
__device__ __forceinline__ unsigned get_tag() { return ld_relaxed(&g_done) / (4 * NCTA) + 1; }
__device__ __forceinline__ unsigned long long ld_tagged(const unsigned long long* p) {
    unsigned long long v; asm volatile("ld.relaxed.gpu.global.b64 %0, [%1];" : "=l"(v) : "l"(p) : "memory"); return v;
}
__device__ __forceinline__ void fence_async() { asm volatile("fence.proxy.async;" ::: "memory"); }
__device__ __forceinline__ void bar_sync(int id, int n) { asm volatile("bar.sync %0, %1;" :: "r"(id), "r"(n) : "memory"); }
__device__ __forceinline__ void bar_arrive(int id, int n) { asm volatile("bar.arrive %0, %1;" :: "r"(id), "r"(n) : "memory"); }
#define ELECT_BEGIN "{\n.reg .pred p, e;\nelect.sync _|p, 0xffffffff;\nsetp.ne.and.u32 e, %1, 0, p;\n@e mbarrier.arrive.expect_tx.shared::cta.b64 _, [%0], %1;\n"
__device__ __forceinline__ void bulk_load(uint32_t dst, const void* src, uint32_t bytes, uint32_t bar, uint32_t tx) {
    asm volatile(ELECT_BEGIN ".reg .b64 pol;\ncreatepolicy.fractional.L2::evict_first.b64 pol, 1.0;\n@p cp.async.bulk.shared::cluster.global.mbarrier::complete_tx::bytes.L2::cache_hint [%2], [%3], %4, [%0], pol;\n}"
        :: "r"(cl(bar)), "r"(tx), "r"(cl(dst)), "l"(src), "r"(bytes) : "memory");
}
__device__ __forceinline__ void send_half(int kb) {
    const uint32_t off = A_OFF + (blockIdx.x & 1) * 8192 + kb * 16384, peer = ((blockIdx.x & 1) ^ 1) << 24;
    asm volatile(ELECT_BEGIN "@p cp.async.bulk.shared::cluster.shared::cta.mbarrier::complete_tx::bytes [%2], [%3], 8192, [%4];\n}"
        :: "r"(cl(BAR_FULLA + 8 * kb)), "r"(8192), "r"(off + peer), "r"(cl(off)), "r"(BAR_FULLA + 8 * kb + peer) : "memory");
}
__device__ __forceinline__ void tma2d(uint32_t dst, const CUtensorMap* m, int c0, int c1, uint32_t bar, uint32_t tx) {
    asm volatile(ELECT_BEGIN "@p cp.async.bulk.tensor.2d.shared::cluster.global.mbarrier::complete_tx::bytes [%2], [%3, {%4, %5}], [%0];\n}"
        :: "r"(cl(bar)), "r"(tx), "r"(cl(dst)), "l"(m), "r"(c0), "r"(c1) : "memory");
}
__device__ __forceinline__ void tma3d(uint32_t dst, const CUtensorMap* m, int c1, int c2, uint32_t bar, uint32_t tx) {
    asm volatile(ELECT_BEGIN "@p cp.async.bulk.tensor.3d.shared::cluster.global.mbarrier::complete_tx::bytes [%2], [%3, {%6, %4, %5}], [%0];\n}"
        :: "r"(cl(bar)), "r"(tx), "r"(cl(dst)), "l"(m), "r"(c1), "r"(c2), "r"(0) : "memory");
}
__device__ __forceinline__ void tma5d(uint32_t dst, const CUtensorMap* m, int c3, int c4, uint32_t bar, uint32_t tx) {
    asm volatile(ELECT_BEGIN "@p cp.async.bulk.tensor.5d.shared::cluster.global.mbarrier::complete_tx::bytes [%2], [%3, {%6, %6, %6, %4, %5}], [%0];\n}"
        :: "r"(cl(bar)), "r"(tx), "r"(cl(dst)), "l"(m), "r"(c3), "r"(c4), "r"(0) : "memory");
}
__device__ __forceinline__ uint32_t pack_bf16(float lo, float hi) {
    uint32_t r; asm("cvt.rn.bf16x2.f32 %0, %1, %2;" : "=r"(r) : "f"(hi), "f"(lo)); return r;
}
__device__ __forceinline__ float bf_lo(uint32_t v) { return __uint_as_float(v << 16); }
__device__ __forceinline__ float bf_hi(uint32_t v) { return __uint_as_float(v & 0xffff0000u); }
__device__ __forceinline__ float2 lds64(uint32_t a) { float2 v; asm volatile("ld.shared.v2.f32 {%0,%1}, [%2];" : "=f"(v.x), "=f"(v.y) : "r"(cl(a))); return v; }
__device__ __forceinline__ uint32_t lds32(uint32_t a) { uint32_t v; asm volatile("ld.shared.u32 %0, [%1];" : "=r"(v) : "r"(cl(a)) : "memory"); return v; }
__device__ __forceinline__ void l2_prefetch(const void* p, uint32_t bytes, uint32_t pause) {
#pragma unroll 1
    for (uint32_t o = (threadIdx.x & 31) * 128; o < bytes; o += 4096) {
        asm volatile("prefetch.global.L2 [%0];" :: "l"((const uint8_t*)p + o) : "memory");
        if (pause) asm volatile("nanosleep.u32 %0;" :: "r"(pause));
    }
    __syncwarp();
}
__device__ __forceinline__ void l2_prefetch_bulk(const void* p, uint32_t bytes) {
    asm volatile("{\n.reg .pred p;\nelect.sync _|p, 0xffffffff;\n@p cp.async.bulk.prefetch.L2.global [%0], %1;\n}" :: "l"(p), "r"(bytes) : "memory");
}
__device__ __forceinline__ float ex2(float x) { float y; asm("ex2.approx.ftz.f32 %0, %1;" : "=f"(y) : "f"(x)); return y; }

__device__ __forceinline__ int cta_m() { return blockIdx.x >> 3; }
__device__ __forceinline__ int cta_j() { return blockIdx.x & 7; }
__device__ __forceinline__ bool cta_isG() { return blockIdx.x < 128 && (blockIdx.x & 7) < 3; }
#define AORDER 0x42310000
__device__ __forceinline__ int cta_aidx() {
    const int j = blockIdx.x & 7;
    return blockIdx.x >= 128 ? blockIdx.x - 128 : 4 + ((AORDER >> (4 * j)) & 7) * 16 + (blockIdx.x >> 3);
}

#define MINIW 0x02022000
__device__ __forceinline__ int mini_w() { return (MINIW >> (4 * cta_j())) & 3; }
__device__ __forceinline__ int has_mini() { return mini_w() != 0; }
__device__ __forceinline__ int num_jobs() { return has_mini() + (cta_isG() ? 4 : 2); }
__device__ __forceinline__ int job_id(int q) {
    const int w = q - has_mini(), j = cta_j();
    const uint32_t below = MINIW & ((1u << (4 * j)) - 1);
    return w < 0 ? __popc(below & 0x11111111u) + 2 * __popc(below & 0x22222222u) : 6 + (w < 2 ? 8 * w + j : 10 + 3 * w + j);
}
__device__ __forceinline__ int job_chunk(int id) { return id < 6 ? id : 3 * id - 12; }
__device__ __forceinline__ int job_bar(int q) { return q < 3 ? 11 + q : (q == 3 ? 15 : 3); }

template<int J>
__device__ __forceinline__ void qkv_mainloop(uint32_t* v, int wg, bool elect) {
    constexpr int O = (216 * J) % 64, N1 = 64 - O, N2 = 152 + O, NCH = (O + 216 + 63) / 64, NST = NCH == 4 ? 9 : 7;
    constexpr uint64_t dB = mkdesc(B_OFF, 2048, 1024, 1);
    const uint64_t dA = mkdesc(A_OFF, 16, 1024, 1) + (uint64_t)((wg - 1) * (8192 >> 4));
    int st = NST == 7 ? 6 : 0; uint32_t ph = 0;
    float acc[108];
#pragma unroll 1
    for (int ks = 0; ks < 36; ks += 2) {
        int st1 = st + 1; uint32_t ph1 = ph; if (st1 == NST) { st1 = 0; ph1 ^= 1; }
        if ((ks & 3) == 0 && ((wg ^ blockIdx.x) & 1) == 0) mbar_wait(BAR_FULLA + 2 * ks, 0);
        mbar_wait(BAR_FULLW + 8 * st, ph);
        mbar_wait(BAR_FULLW + 8 * st1, ph1);
        const uint64_t a = dA + (uint64_t)((ks >> 2) * (16384 >> 4) + (ks & 3) * 2);
        WG_FENCE();
#pragma unroll
        for (int k = 0; k < 2; k++) {
            const uint64_t b = dB + (uint64_t)((k ? st1 : st) * (NCH * 2048 >> 4));
            if (N2 <= 200) mma_ssp<(N2 <= 200 ? N2 : 128)>(acc + N1 / 2, a + 2 * k, b + (2048 >> 4), ks + k);
            else { mma_ssp<128>(acc + N1 / 2, a + 2 * k, b + (2048 >> 4), ks + k); mma_ssp<80>(acc + N1 / 2 + 64, a + 2 * k, b + (6144 >> 4), ks + k); }
            mma_ssp<N1>(acc, a + 2 * k, b + (2 * O >> 4), ks + k);
        }
        WG_COMMIT();
        WG_WAIT(1);
        if ((threadIdx.x & 127) < 2 && ks > 0) {
            int sp = st - 1 - (threadIdx.x & 1); if (sp < 0) sp += NST;
            mbar_arrive(BAR_EMPTYW + 8 * sp);
        }
        st = st1 + 1; ph = ph1; if (st == NST) { st = 0; ph ^= 1; }
    }
    WG_WAIT(0);
    keep<108>(acc);
    if ((threadIdx.x & 127) < 3) mbar_arrive((threadIdx.x & 127) == 2 ? BAR_WDONE : BAR_EMPTYW + 8 * (NST - 1 - (threadIdx.x & 1)));
    if (wg == 1) TS(16);
    constexpr float QS = 0.23570226f * 1.44269504f;
#pragma unroll
    for (int i = 0; i < 54; i++) v[i] = 216 * J + 8 * (i >> 1) < DM ? pack_bf16(acc[2 * i] * QS, acc[2 * i + 1] * QS) : pack_bf16(acc[2 * i], acc[2 * i + 1]);
}

__device__ __forceinline__ uint64_t sel_desc(int q) { return mkdesc(ONE_OFF, 0, 0, 0) + (uint64_t)(q * (128 >> 4)) + ((uint64_t)((6 - q) * (128 >> 4)) << 16); }
constexpr uint64_t SEL2 = (uint64_t)(128 >> 4) << 16;
constexpr uint64_t BIAS_DESC = mkdesc(BIAS_OFF, 1024, 0, 1);
template<int W>
__device__ __forceinline__ void mini_mainloop(float* acc0, float* acc1, bool elect) {
    constexpr uint64_t dA = mkdesc(A_OFF, 16, 1024, 1), dB = mkdesc(B_OFF, 6144, 1024, 1);
    WG_FENCE();
    if (W == 1) { mma_n64_ss<0>(acc0, sel_desc(0), BIAS_DESC); mma_n64_ss<0>(acc1, sel_desc(0) + SEL2, BIAS_DESC); }
    else { mma_n128_ss<0>(acc0, sel_desc(0), BIAS_DESC); mma_n128_ss<0>(acc1, sel_desc(0) + SEL2, BIAS_DESC); }
    WG_COMMIT();
    int st = 0;
#pragma unroll 1
    for (int s = 0; s < 6 * W; s++) {
        mbar_wait(BAR_FULLB + 8 * st, s >= 6);
        if (s == 6 * W - 1) bar_arrive(9, 256);
        WG_FENCE();
#pragma unroll
        for (int k = 0; k < 6 / W; k++) {
            const int ks = (6 / W) * s + k;
            const uint64_t a = dA + (uint64_t)((ks >> 2) * (16384 >> 4) + (ks & 3) * 2), b = dB + (uint64_t)(st * (12288 >> 4) + k * (2048 >> 4));
            if (W == 1) { mma_n64_ss<1>(acc0, a, b); mma_n64_ss<1>(acc1, a + (8192 >> 4), b); }
            else { mma_n128_ss<1>(acc0, a, b); mma_n128_ss<1>(acc1, a + (8192 >> 4), b); }
        }
        WG_COMMIT();
        WG_WAIT(1);
        if (elect && s > 0) mbar_arrive(BAR_EMPTYB + 8 * (st == 0 ? 5 : st - 1));
        if (++st == 6) st = 0;
    }
    WG_WAIT(0);
    if (elect) mbar_arrive(BAR_EMPTYB + 8 * 5);
    keep<32 * W>(acc0); keep<32 * W>(acc1);
}
__device__ __forceinline__ void job_mainloop(float* acc0, float* acc1, int q, bool g2, uint32_t xa, bool elect) {
    constexpr uint64_t dB = mkdesc(B_OFF, 4096, 1024, 1);
    const bool last = q == num_jobs() - 1, releaseA = g2 || last, handoff = !g2 && (!last || cta_isG());
    WG_FENCE();
    mma_n192_ss<0>(acc0, sel_desc(g2 ? 5 : q), BIAS_DESC); mma_n192_ss<0>(acc1, sel_desc(g2 ? 5 : q) + SEL2, BIAS_DESC);
    WG_COMMIT();
    if (q > 0) bar_sync(8 + (q & 1), 256);
    const int nturn = g2 ? 27 : 3;
    int grp = 0; uint32_t pa = 1;
#pragma unroll 1
    for (int u = 0; u < nturn; u++) {
        const uint32_t par = (q + u + (mini_w() >> 1)) & 1;
        if (g2 && (u == 3 || u == 12 || u == 24)) TS2(u == 3 ? 4 : (u == 12 ? 5 : 6));
        if (u == 24) {
            mbar_wait(BAR_FULLA, pa); mbar_wait(BAR_FULLA + 8, pa); mbar_wait(BAR_FULLA + 16, pa);
            WG_WAIT(0);
            keep<96>(acc0); keep<96>(acc1);
            if (elect) { mbar_arrive(BAR_EMPTYB + 8 * 5); mbar_arrive(BAR_EMPTYA + 8 * 8); }
#pragma unroll
            for (int i2 = 0; i2 < 12; i2++) {
#pragma unroll
                for (int mh = 0; mh < 2; mh++) {
                    float* a = (mh ? acc1 : acc0) + 8 * i2;
                    uint32_t r[4];
                    asm volatile("ldmatrix.sync.aligned.m8n8.x4.shared.b16 {%0,%1,%2,%3}, [%4];" : "=r"(r[0]), "=r"(r[1]), "=r"(r[2]), "=r"(r[3])
                        : "r"(cl((xa ^ ((i2 & 3) << 5)) + (i2 >> 2) * 16384 + mh * 8192)) : "memory");
#pragma unroll
                    for (int e = 0; e < 4; e++) { a[2 * e] = fmaf(a[2 * e], 0.5f, bf_lo(r[e])); a[2 * e + 1] = fmaf(a[2 * e + 1], 0.5f, bf_hi(r[e])); }
                }
            }
            keep<96>(acc0); keep<96>(acc1);
            grp = 1;
        }
        const uint64_t dAu = (!g2 ? mkdesc(A_OFF, 16, 1024, 1) : (u < 24 ? mkdesc(A_OFF, 16, 512, 2) : mkdesc(A_OFF, 128, 1024, 0))) + (uint64_t)(grp * (3 * 16384 >> 4));
        const uint32_t kst = u >= 24 ? (256 >> 4) : (32 >> 4), hst = !g2 ? (64 >> 4) : (u < 24 ? (8192 >> 4) : (512 >> 4)), mst = (g2 && u < 24) ? (4096 >> 4) : (8192 >> 4);
#pragma unroll
        for (int st = 0; st < 6; st++) {
            const int kb = st >> 1, half = st & 1;
            if (half == 0 && g2) mbar_wait(BAR_FULLA + 8 * (3 * grp + kb), pa);
            mbar_wait(BAR_FULLB + 8 * st, par);
            if (st == 5 && u == 2 && handoff) bar_arrive(8 + ((q + 1) & 1), 256);
            WG_FENCE();
#pragma unroll
            for (int k = 0; k < 2; k++) {
                const uint64_t a = dAu + (uint64_t)(kb * (16384 >> 4) + half * hst + k * kst);
                const uint64_t b = dB + (uint64_t)((st * 12288 + k * 2048) >> 4);
                mma_n192_ss<1>(acc0, a, b); mma_n192_ss<1>(acc1, a + mst, b);
            }
            WG_COMMIT();
            WG_WAIT(1);
            if (elect && (st > 0 || u > 0)) {
                if (st > 0 || u != 24) {
                    mbar_arrive(BAR_EMPTYB + 8 * ((st + 5) % 6));
                    if (half == 0 && releaseA) mbar_arrive(BAR_EMPTYA + 8 * (kb == 0 && grp == 0 ? 8 : 3 * grp + kb - 1));
                }
                if (st == 1 && u == 24) { mbar_arrive(BAR_EMPTYA); mbar_arrive(BAR_EMPTYA + 8); mbar_arrive(BAR_EMPTYA + 16); }
            }
        }
        if (++grp == 3) { grp = 0; pa ^= 1; }
    }
    WG_WAIT(0);
    if (elect && !g2) { mbar_arrive(BAR_EMPTYB + 8 * 5); if (releaseA) mbar_arrive(BAR_EMPTYA + 8 * 8); }
    keep<96>(acc0); keep<96>(acc1);
}

__device__ __forceinline__ void epilogue_gelu(const float* acc, uint8_t* hp, int nchunk) {
#pragma unroll
    for (int i4 = 0; i4 < 6; i4++) {
        if ((i4 == 2 || i4 == 4) && i4 == 2 * nchunk) break;
        float z[16];
#define XX(e) acc[4 * (8 * (i4 >> 1) + (i4 & 1) + 2 * ((e) >> 2)) + ((e) & 3)]
#pragma unroll
        for (int e = 0; e < 16; e++) z[e] = XX(e) * fmaf(XX(e) * XX(e), 0.035677408f, 0.79788456f);
#pragma unroll
        for (int e = 0; e < 16; e++) asm("tanh.approx.f32 %0, %0;" : "+f"(z[e]));
#pragma unroll
        for (int e = 0; e < 16; e++) z[e] = fmaf(XX(e), z[e], XX(e));
#undef XX
#pragma unroll
        for (int r = 0; r < 2; r++)
            *(uint4*)(hp + r * 512 + i4 * 8192) = make_uint4(pack_bf16(z[2 * r], z[2 * r + 1]), pack_bf16(z[4 + 2 * r], z[5 + 2 * r]),
                                                                         pack_bf16(z[8 + 2 * r], z[9 + 2 * r]), pack_bf16(z[12 + 2 * r], z[13 + 2 * r]));
    }
}
__device__ __forceinline__ void job_epilogue(float* acc0, float* acc1, int q, int warp, int g, int t) {
    uint8_t* hp = g_h + (size_t)(cta_m() * 72 + job_chunk(job_id(q))) * 16384 + warp * 1024 + g * 64 + ((t ^ (g >> 1)) << 4);
    epilogue_gelu(acc0, hp, q < has_mini() ? mini_w() : 3);
    epilogue_gelu(acc1, hp + 4096, q < has_mini() ? mini_w() : 3);
    kill<96>(acc0); kill<96>(acc1);
    bar_arrive(job_bar(q), 160);
}

__device__ __forceinline__ void epilogue_qkv(const uint32_t* vv, int rg, int g, int t, int wg) {
    const int j = cta_j();
#define V(r, i) vv[2 * (i) + (r)]
    if (wg == 2 && !has_mini()) bar_sync(14, 256);
    uint8_t* p = g_qkv + (size_t)(12 * j) * 98304 + rg * 384 + g * 16;
    const uint32_t pk0 = ((POLYMASK >> (rg & 15)) & 1) ? 0x3f803f80u : 0u, pk1 = ((POLYMASK >> ((rg + 1) & 15)) & 1) ? 0x3f803f80u : 0u;
#pragma unroll
    for (int gi = 0; gi < 3; gi++) {
        const int which = (3 * j + gi) >> 3;
        const uint32_t ec = which == 2 ? 0x00003f80u : 0x427e4740u, ed = which == 2 ? 0u : 0x3aacbe9au, hs = which == 0 ? 0x3f003f00u : 0x3f803f80u;
        const uint32_t ea0 = which == 1 ? pk0 : ec, ea1 = which == 1 ? pk1 : ec, eb0 = which == 1 ? pk0 : ed, eb1 = which == 1 ? pk1 : ed;
        uint32_t mx[2] = {0u, 0u};
#pragma unroll
        for (int h = 4 * gi; h < 4 * gi + 4; h++) {
            {
                const int k = (9 * h) % 4, i0 = (9 * h) / 4, r = (t - k) & 3;
                const int off = h * 98304 + (r >> 1) * 128 + (r & 1) * 8;
                const bool lo = k == 0 || t >= k;
                *(uint2*)(p + off) = make_uint2(lo ? V(0, i0) : V(0, i0 + 1), lo ? V(0, i0 + 1) : V(0, i0 + 2));
                *(uint2*)(p + off + 384) = make_uint2(lo ? V(1, i0) : V(1, i0 + 1), lo ? V(1, i0 + 1) : V(1, i0 + 2));
            }
            if (t == (9 * h + 8) % 4) {
                uint32_t u0, u1;
                asm("mul.rn.bf16x2 %0, %1, %2;" : "=r"(u0) : "r"(V(0, (9 * h + 8) / 4)), "r"(hs));
                asm("mul.rn.bf16x2 %0, %1, %2;" : "=r"(u1) : "r"(V(1, (9 * h + 8) / 4)), "r"(hs));
                *(uint4*)(p + h * 98304 + 256) = make_uint4(u0, ea0, eb0, 0u);
                *(uint4*)(p + h * 98304 + 256 + 384) = make_uint4(u1, ea1, eb1, 0u);
            }
#pragma unroll
            for (int r = 0; r < 2; r++) {
                const int b0 = (9 * h) / 4;
                uint32_t a;
                asm("mul.rn.bf16x2 %0, %1, %1;" : "=r"(a) : "r"(V(r, b0)));
                asm("fma.rn.bf16x2 %0, %1, %1, %0;" : "+r"(a) : "r"(V(r, b0 + 1)));
                asm("fma.rn.bf16x2 %0, %1, %1, %0;" : "+r"(a) : "r"(V(r, b0 + 2)));
                asm("max.NaN.bf16x2 %0, %0, %1;" : "+r"(mx[r]) : "r"(a));
            }
        }
        float w0 = bf_lo(mx[0]) + bf_hi(mx[0]), w1 = bf_lo(mx[1]) + bf_hi(mx[1]);
        w0 += __shfl_xor_sync(0xffffffffu, w0, 1); w1 += __shfl_xor_sync(0xffffffffu, w1, 1);
        w0 += __shfl_xor_sync(0xffffffffu, w0, 2); w1 += __shfl_xor_sync(0xffffffffu, w1, 2);
        const uint32_t bb = __reduce_max_sync(0xffffffffu, max(__float_as_uint(w0) & 0x7fffffffu, __float_as_uint(w1) & 0x7fffffffu));
        if ((threadIdx.x & 31) == 0) asm volatile("red.shared.max.u32 [%0], %1;" :: "r"(cl(BMAX_OFF + 4 * gi)), "r"(bb) : "memory");
    }
}

__device__ __forceinline__ uint32_t exp2_fma(float a, float b, uint32_t c3f00, uint32_t c0003) {
    uint32_t s, m, e, r;
    asm("prmt.b32 %0, %1, %2, 0x5410;" : "=r"(s) : "r"(__float_as_uint(a)), "r"(__float_as_uint(b)));
    asm("lop3.b32 %0, %1, 0x007f007f, %2, 0xEA;" : "=r"(m) : "r"(s), "r"(c3f00));
    asm("lop3.b32 %0, %1, 0xff80ff80, %2, 0xEA;" : "=r"(e) : "r"(s), "r"(c0003));
    asm("fma.rn.bf16x2 %0, %1, %2, %3;" : "=r"(r) : "r"(s), "r"(m), "r"(e));
    return r;
}
template<int B0> __device__ __forceinline__ void exps(const float* S, uint32_t* P, uint32_t c3f00, uint32_t c0003) {
#pragma unroll
    for (int i = 0; i < 4; i++) {
        if ((POLYMASK >> (i + B0)) & 1) { P[2 * i] = exp2_fma(S[4 * i], S[4 * i + 1], c3f00, c0003); P[2 * i + 1] = exp2_fma(S[4 * i + 2], S[4 * i + 3], c3f00, c0003); }
        else { P[2 * i] = pack_bf16(ex2(S[4 * i]), ex2(S[4 * i + 1])); P[2 * i + 1] = pack_bf16(ex2(S[4 * i + 2]), ex2(S[4 * i + 3])); }
    }
}
__device__ __forceinline__ void pv(float* O, const uint32_t* X, const uint32_t* Y, uint64_t dv) {
    mma_n24_rs<1>(O, X[0], X[1], X[2], X[3], dv); mma_n24_rs<1>(O, X[4], X[5], X[6], X[7], dv + (768 >> 4));
    mma_n24_rs<1>(O, Y[0], Y[1], Y[2], Y[3], dv + 2 * (768 >> 4)); mma_n24_rs<1>(O, Y[4], Y[5], Y[6], Y[7], dv + 3 * (768 >> 4));
}
constexpr uint64_t STEP2 = (256 >> 4) - ((uint64_t)(128 >> 4) << 16);
__device__ __forceinline__ void qk(float* S, uint64_t dq, uint64_t dk) {
    mma_n64_sk<0>(S, dq, dk);
    mma_n64_sk<1>(S, dq + STEP2, dk + STEP2);
}
__device__ __forceinline__ void qk_rs(float* S, const uint32_t* q, uint64_t dk) {
    mma_n64_rs<0>(S, q[0], q[1], q[2], q[3], dk);
    mma_n64_rs<1>(S, q[4], q[5], q[6], q[7], dk + STEP2);
}
__device__ __forceinline__ int helper_id() {
    const int j = cta_j(), h = cta_m() + (j == 7 ? 0 : 16);
    return (blockIdx.x < 128 && (j == 7 || j == HELP2) && h < 4 * XS) ? h : -1;
}
__device__ __forceinline__ int num_tasks() { return blockIdx.x >= 128 ? 32 - XS : (helper_id() >= 0 ? 25 : 24); }
__device__ __forceinline__ void seg_info(int seg, int& rd, int& s0, int& len) {
    const int h = helper_id();
    rd = cta_aidx() + NACTA * (h >= 0 ? seg - 1 : seg); s0 = 0; len = 8;
    if (h >= 0 && seg == 0) { rd = 252 + (h & 3); s0 = h >> 2; len = 1; }
    if (rd >= 252 && h < 0) { s0 = XS; len = 8 - XS; }
}
__device__ __forceinline__ void task_table(int task) {
    int seg = task >> 3, k = task & 7;
    if (helper_id() >= 0 && task >= 1) { seg = 1 + ((task - 1) >> 3); k = (task - 1) & 7; }
    int rd, s0, len; seg_info(seg, rd, s0, len);
    const uint32_t hb = (rd >> 3) * 98304;
    asm volatile("st.shared.v2.u32 [%0], {%1, %2};" :: "r"(cl(TASK_OFF + 8 * task)), "r"(hb + 32 * 98304 + (s0 + k) * 12288),
                 "r"(k == 0 ? hb + (rd & 7) * 12288 + 2 + (seg & 1) : 0) : "memory");
}
__device__ __forceinline__ void kv_load(int task) {
    const float2 e = lds64(TASK_OFF + 8 * task);
    const uint32_t ko = __shfl_sync(0xffffffffu, __float_as_uint(e.x), 0), qo = __shfl_sync(0xffffffffu, __float_as_uint(e.y), 0);
    const int sl = task & 7;
    bulk_load(K_OFF + sl * 12288, g_qkv + ko, 12288, BAR_FULLKV + 8 * sl, qo ? 36864 : 24576);
    bulk_load(V_OFF + sl * 12288, g_qkv + ko + 32 * 98304, 12288, BAR_FULLKV + 8 * sl, 0);
    if (qo) bulk_load((qo & 1) ? Q2_OFF : Q_OFF, g_qkv + (qo & ~3u), 12288, BAR_FULLKV + 8 * sl, 0);
}
__device__ __forceinline__ void kv_refill(int task, int wg, int ntask) {
    const int r = task + 8 - KVLAG;
    if ((r & 3) == wg && r >= 8 && r < ntask) {
        mbar_wait(BAR_EMPTYKV + 8 * (r & 7), ((r >> 3) & 1) ^ 1);
        kv_load(r);
    }
}
__device__ __forceinline__ void publish_all(unsigned* flag0, int stride, int seg, unsigned tag) {
    mbar_wait(BAR_DEP + 8 * (seg & 1), (seg >> 1) & 1);
    if ((threadIdx.x & 31) < 4) st_release(flag0 + (threadIdx.x & 31) * stride, tag);
    __syncwarp();
}

__device__ __forceinline__ void pieces_acquire(int wg, unsigned tag) {
    const int lane = threadIdx.x & 31, r = blockIdx.x - 128;
    int n = 0;
    while (!__all_sync(0xffffffffu, ld_acquire(&g_pflag[(r * 4 + wg) * 8 + lane % XS]) == tag))
        asm volatile("{\n.reg .pred q;\nnanosleep.u32 100;\nsetp.gt.u32 q, %0, 4000000;\n@q trap;\n}" :: "r"(++n));
#pragma unroll 1
    for (int i = lane; i < XS * 64; i += 32)
        asm volatile("prefetch.global.L2 [%0];" :: "l"(g_part + (r * XS * 4 + (i >> 4)) * 512 + wg * 128 + (i & 15) * 8) : "memory");
}

__device__ __forceinline__ void attention(int wg, unsigned tag) {
    const int lane = threadIdx.x & 31, t = lane & 3;
    const int warp = __shfl_sync(0xffffffffu, (threadIdx.x >> 5) & 3, 0);
    const bool elect = (threadIdx.x & 127) == 0;
    constexpr uint64_t dk0 = mkdesc(K_OFF, 128, 384, 0), dv0 = mkdesc(V_OFF, 384, 128, 0);
    const uint32_t zero = (blockIdx.x >> 20) * lane;
    const uint32_t c3f00 = __shfl_sync(0xffffffffu, 0x3f003f00u + zero, 0);
    const uint32_t c0003 = __shfl_sync(0xffffffffu, 0x00030003u + zero, 0);
    unsigned* pending = nullptr; int pstride = 0;
    const int ntask = num_tasks();
    int T = 0;
#pragma unroll 1
    for (int seg = 0; T < ntask; seg++) {
        int rd, s0, len; seg_info(seg, rd, s0, len);
        const int Tend = T + len, Tpub = (seg > 0 && (seg & 3) == wg && ((warp + wg) & 3) == 2) ? (len < 4 ? Tend - 1 : T + 3) : -1;
        mbar_wait(BAR_FULLKV + 8 * (T & 7), (T >> 3) & 1);
        const bool fast = (__shfl_sync(0xffffffffu, lds32(FAST_OFF), 0) >> (rd >> 5)) & 1;
        const uint64_t q = mkdesc(Q_OFF, 128, 384, 0) + (uint64_t)((((seg & 1) ? Q2_OFF - Q_OFF : 0) + wg * 3072) >> 4);
        float m0 = 0.f, m1 = 0.f;
        float SA[32], SB_[32], O[12];
        uint32_t P[16];
#pragma unroll
        for (int i = 0; i < 12; i++) O[i] = 0.f;
        if (!fast) m0 = m1 = -INFINITY;
        if (len != 8 && len != 1) {
            bar_sync(4 + wg, 128);
            float4 pa[XS][4];
#pragma unroll
            for (int i = 0; i < XS; i++) {
                const float4* pp = g_part + ((rd - 252) * XS + i) * 2048 + threadIdx.x;
#pragma unroll
                for (int e = 0; e < 4; e++) pa[i][e] = __ldcg(pp + 512 * e);
            }
#pragma unroll
            for (int i = 0; i < XS; i++) {
                const float4 a = pa[i][0], b = pa[i][1], c = pa[i][2], m = pa[i][3];
                const float n0 = fmaxf(m0, m.x), n1 = fmaxf(m1, m.y);
                const float f0 = ex2(m0 - n0), f1 = ex2(m1 - n1), g0 = ex2(m.x - n0), g1 = ex2(m.y - n1);
                m0 = n0; m1 = n1;
                O[0] = O[0] * f0 + a.x * g0; O[1] = O[1] * f0 + a.y * g0; O[2] = O[2] * f1 + a.z * g1; O[3] = O[3] * f1 + a.w * g1;
                O[4] = O[4] * f0 + b.x * g0; O[5] = O[5] * f0 + b.y * g0; O[6] = O[6] * f1 + b.z * g1; O[7] = O[7] * f1 + b.w * g1;
                O[8] = O[8] * f0 + c.x * g0; O[9] = O[9] * f0 + c.y * g0; O[10] = O[10] * f1 + c.z * g1; O[11] = O[11] * f1 + c.w * g1;
            }
        }
#pragma unroll
        for (int i = 0; i < 12; i++) asm volatile("add.f32 %0, %0, %1;" : "+f"(O[i]) : "f"(__uint_as_float(zero)) : "memory");
        if (fast) {
            uint64_t dk = dk0 + (uint64_t)((T & 7) * (12288 >> 4)), dv = dv0 + (uint64_t)((T & 7) * (12288 >> 4));
            WG_FENCE();
            qk(SA, q, dk); WG_COMMIT();
            qk(SB_, q, dk + (3072 >> 4)); WG_COMMIT();
            dk += 2 * (3072 >> 4);
            const int role = (warp + wg) & 3;
            const uint32_t duty = role == 0 ? ~0u << (T + 1) : (role == 1 ? 0x11111111u << ((wg + KVLAG) & 3) : (Tpub >= 0 ? 1u << Tpub : (role == 3 && blockIdx.x >= 128 ? 1u << 22 : 0u)));
#pragma unroll 1
            for (; T < Tend; T++) {
                const uint32_t wrap = (T & 7) == 7 ? (8 * 12288 >> 4) : 0;
#pragma unroll
                for (int h = 0; h < 4; h++) {
                    float* S = (h & 1) ? SB_ : SA;
                    WG_WAIT(1);
                    keep<32>(S); keep<12>(O);
                    if (h & 1) { exps<8>(S, P, c3f00, c0003); exps<12>(S + 16, P + 8, c3f00, c0003); } else { exps<0>(S, P, c3f00, c0003); exps<4>(S + 16, P + 8, c3f00, c0003); }
                    keep<16>(P);
                    WG_FENCE();
                    pv(O, P, P + 8, dv); WG_COMMIT();
                    qk(S, q, dk); WG_COMMIT();
                    dv += (3072 >> 4); dk += (3072 >> 4);
                    if (h == 1) { dk -= wrap; if (T + 1 < Tend) mbar_wait_raw(cl(BAR_FULLKV) + 8 * ((T + 1) & 7), ((T + 1) >> 3) & 1); }
                    if (h == 3) dv -= wrap;
                    if (h == 0 && ((duty >> T) & 1)) {
                        if (role == 0) { if (lane == 0) mbar_arrive(BAR_EMPTYKV + 8 * ((T - 1) & 7)); __syncwarp(); }
                        else if (role == 1) kv_refill(T, wg, ntask);
                        else if (role == 2) publish_all(pending, pstride, seg - 1, tag);
                        else pieces_acquire(wg, tag);
                    }
                }
            }
            WG_WAIT(0);
            keep<12>(O); keep<32>(SA); keep<32>(SB_);
            m0 = m1 = 0.f;
        } else {
            const uint32_t qa = ((seg & 1) ? Q2_OFF : Q_OFF) + (wg * 8 + warp * 2) * 384 + lane * 4;
            uint32_t qr[8];
            qr[0] = lds32(qa); qr[1] = lds32(qa + 384); qr[2] = lds32(qa + 128); qr[3] = lds32(qa + 384 + 128);
            qr[4] = lds32(qa + 256 + (t ? 12 - 4 * t : 0)); qr[5] = lds32(qa + 384 + 256 + (t ? 12 - 4 * t : 0));
            qr[6] = lds32(qa + 256 + (t ? 12 - 4 * t : 0)); qr[7] = lds32(qa + 384 + 256 + (t ? 12 - 4 * t : 0));
            keep<8>(qr);
#pragma unroll 1
            for (; T < Tend; T++) {
                if (warp == 1) kv_refill(T, wg, ntask);
                if (T == Tpub) publish_all(pending, pstride, seg - 1, tag);
                if (T == 22 && warp == 3 && blockIdx.x >= 128) pieces_acquire(wg, tag);
                mbar_wait(BAR_FULLKV + 8 * (T & 7), (T >> 3) & 1);
#pragma unroll 1
                for (int h = 0; h < 4; h++) {
                    const uint64_t so = (uint64_t)(((T & 7) * 12288 + h * 3072) >> 4);
                    WG_FENCE();
                    qk_rs(SA, qr, dk0 + so); WG_COMMIT();
                    WG_WAIT(0);
                    keep<32>(SA); keep<12>(O);
                    float n0 = m0, n1 = m1;
#pragma unroll
                    for (int i = 0; i < 8; i++) { n0 = fmaxf(n0, fmaxf(SA[4 * i], SA[4 * i + 1])); n1 = fmaxf(n1, fmaxf(SA[4 * i + 2], SA[4 * i + 3])); }
                    n0 = fmaxf(n0, __shfl_xor_sync(0xffffffffu, n0, 1)); n0 = fmaxf(n0, __shfl_xor_sync(0xffffffffu, n0, 2));
                    n1 = fmaxf(n1, __shfl_xor_sync(0xffffffffu, n1, 1)); n1 = fmaxf(n1, __shfl_xor_sync(0xffffffffu, n1, 2));
                    const float f0 = ex2(m0 - n0), f1 = ex2(m1 - n1);
                    m0 = n0; m1 = n1;
#pragma unroll
                    for (int i = 0; i < 3; i++) { O[4 * i] *= f0; O[4 * i + 1] *= f0; O[4 * i + 2] *= f1; O[4 * i + 3] *= f1; }
#pragma unroll
                    for (int i = 0; i < 8; i++) {
                        P[2 * i] = pack_bf16(ex2(SA[4 * i] - m0), ex2(SA[4 * i + 1] - m0));
                        P[2 * i + 1] = pack_bf16(ex2(SA[4 * i + 2] - m1), ex2(SA[4 * i + 3] - m1));
                    }
                    keep<16>(P); keep<12>(O);
                    WG_FENCE();
                    pv(O, P, P + 8, dv0 + so); WG_COMMIT();
                    WG_WAIT(0);
                    keep<12>(O);
                }
                if (elect && T + 1 < Tend) mbar_arrive(BAR_EMPTYKV + 8 * (T & 7));
            }
        }
        if (elect) mbar_arrive(BAR_EMPTYKV + 8 * ((T - 1) & 7));
        if (wg == 1) TS2(4 + seg);
        if (len == 1) {
            float4* pp = g_part + ((rd - 252) * XS + s0) * 2048 + threadIdx.x;
            pp[0] = make_float4(O[0], O[1], O[2], O[3]); pp[512] = make_float4(O[4], O[5], O[6], O[7]);
            pp[1024] = make_float4(O[8], O[9], O[10], O[11]); pp[1536] = make_float4(m0, m1, 0.f, 0.f);
            pending = &g_pflag[(rd - 252) * 32 + s0]; pstride = 8;
            __syncwarp();
            if (lane == 0) mbar_arrive(BAR_DEP + 8 * (seg & 1));
            continue;
        }
        const int head = rd >> 3, rb = (rd & 7) * 4 + wg, g = lane >> 2;
        const float l0 = __shfl_sync(0xffffffffu, O[8], (lane & ~3) | 1), l1 = __shfl_sync(0xffffffffu, O[10], (lane & ~3) | 1);
        const float r0 = __frcp_rn(l0), r1 = __frcp_rn(l1);
        uint8_t* ob = g_o + (size_t)(rb >> 1) * (9 * 16384) + ((rb & 1) * 8 + warp * 2) * 1024 + g * 16;
#pragma unroll
        for (int i = 0; i < 3; i++) {
            const int c = head * 18 + (i < 2 ? 4 * i + (t & 2) + 8 * (t & 1) : 16);
            uint8_t* op = ob + (c >> 6) * 16384 + ((c >> 3) & 7) * 128 + (c & 7) * 2;
            if (i < 2 || t == 0) {
                *(uint32_t*)op = pack_bf16(O[4 * i] * r0, O[4 * i + 1] * r0);
                *(uint32_t*)(op + 1024) = pack_bf16(O[4 * i + 2] * r1, O[4 * i + 3] * r1);
            }
        }
        pending = &g_oflag[(rd & 7) * 128 + head]; pstride = 32;
        __syncwarp();
        if (lane == 0) mbar_arrive(BAR_DEP + 8 * (seg & 1));
    }
    bar_sync(4 + wg, 128);
    if (elect) st_release(pending + wg * pstride, tag);
}

__global__ void __cluster_dims__(2, 1, 1) __launch_bounds__(NTHREADS, 1) fused_kernel(const __grid_constant__ Params p) {
    extern __shared__ __align__(1024) uint8_t smem_raw[];
    if ((uint32_t)__cvta_generic_to_shared(smem_raw) != cl(SB)) asm volatile("trap;");
    const int wg = __shfl_sync(0xffffffffu, threadIdx.x >> 7, 0);
    const int lane = threadIdx.x & 31;
    const bool elect = (threadIdx.x & 127) == 0;
    const bool gemm = blockIdx.x < 128;
    const bool five = cta_j() == 2 || cta_j() == 5;
    if (threadIdx.x >= 32 && threadIdx.x < 41) asm volatile("prefetch.tensormap [%0];" :: "l"(&p.wq4 + (threadIdx.x - 32)) : "memory");
    const int lrow = (blockIdx.x & 1) * 64 + (threadIdx.x >> 3);
    uint32_t v[36];
    if (gemm) {
        const uint4* xr = (const uint4*)(p.xp + (size_t)(cta_m() * 128 + lrow) * DM) + (lane & 7);
#pragma unroll
        for (int i = 0; i < 9; i++) { const uint4 w = __ldg(xr + i * 8); v[4 * i] = w.x; v[4 * i + 1] = w.y; v[4 * i + 2] = w.z; v[4 * i + 3] = w.w; }
        if (threadIdx.x >= 384 && threadIdx.x < 506 && blockIdx.x * 15616 + (threadIdx.x - 384) * 128 < 1728 * DM * 2)
            asm volatile("prefetch.global.L2 [%0];" :: "l"((const uint8_t*)p.wqkvp + blockIdx.x * 15616 + (threadIdx.x - 384) * 128) : "memory");
    }
    if ((threadIdx.x & 31) < NBARS / 16) {
        const int i = (threadIdx.x >> 5) * (NBARS / 16) + (threadIdx.x & 31);
        const uint32_t cnt = (i >= 55 && i < 64) || i == 79 ? 2 : (i >= 38 && i < 46 ? 4 : ((i == 66 || i == 67) && !cta_isG() ? 16 : 1));
        mbar_init(BAR_OFF + 8 * i, cnt);
        asm volatile("fence.mbarrier_init.release.cluster;" ::: "memory");
    }
    if (threadIdx.x >= 40 && threadIdx.x < 43) asm volatile("st.shared.u32 [%0], %1;" :: "r"(cl(BMAX_OFF + 4 * (threadIdx.x - 40))), "r"(0) : "memory");
    __syncthreads();
    asm volatile("barrier.cluster.arrive.relaxed.aligned;" ::: "memory");
    TS(wg);
    if (gemm) {
        const int ks = __shfl_sync(0xffffffffu, threadIdx.x >> 5, 0);
        if (ks < (five ? 7 : 9)) {
            const int st = five ? (ks == 0 ? 6 : ks - 1) : ks;
            if (five && ks > 0 && lane < 3) mbar_arrive(lane == 0 ? BAR_FULLW + 8 * st : BAR_EMPTYW + 8 * st);
            __syncwarp();
            tma3d(B_OFF + st * (five ? 10240 : 8192), five ? &p.wq5 : &p.wq4, ks * 16, (216 * cta_j()) >> 6, BAR_FULLW + 8 * st, five ? 10240 : 8192);
        }
        float f[72], s = 0.f, s2 = 0.f;
#pragma unroll
        for (int i = 0; i < 36; i++) { f[2 * i] = bf_lo(v[i]); f[2 * i + 1] = bf_hi(v[i]); s += f[2 * i]; s2 += f[2 * i + 1]; }
        s += s2;
        s += __shfl_xor_sync(0xffffffffu, s, 1); s += __shfl_xor_sync(0xffffffffu, s, 2); s += __shfl_xor_sync(0xffffffffu, s, 4);
        const float mean = s * (1.0f / DM);
        if (wg == 1) TS(29);
        float q = 0.f, q2 = 0.f;
#pragma unroll
        for (int i = 0; i < 36; i++) { f[2 * i] -= mean; f[2 * i + 1] -= mean; q = fmaf(f[2 * i], f[2 * i], q); q2 = fmaf(f[2 * i + 1], f[2 * i + 1], q2); }
        q += q2;
        q += __shfl_xor_sync(0xffffffffu, q, 1); q += __shfl_xor_sync(0xffffffffu, q, 2); q += __shfl_xor_sync(0xffffffffu, q, 4);
        const float rstd = rsqrtf(q * (1.0f / DM) + 1e-5f);
        const uint32_t dst = cl(A_OFF + lrow * 128 + (((lane & 7) ^ (lrow & 7)) << 4));
#pragma unroll
        for (int i = 0; i < 9; i++)
            asm volatile("st.shared.v4.b32 [%0], {%1,%2,%3,%4};" :: "r"(dst + i * 16384),
                "r"(pack_bf16(f[8 * i] * rstd, f[8 * i + 1] * rstd)), "r"(pack_bf16(f[8 * i + 2] * rstd, f[8 * i + 3] * rstd)),
                "r"(pack_bf16(f[8 * i + 4] * rstd, f[8 * i + 5] * rstd)), "r"(pack_bf16(f[8 * i + 6] * rstd, f[8 * i + 7] * rstd)) : "memory");
        if (wg == 1) TS(31);
        asm volatile("fence.proxy.async.shared::cta;" ::: "memory");
    }
    asm volatile("barrier.cluster.wait.aligned;" ::: "memory");
    __syncthreads();
    if (gemm && threadIdx.x < 32) { send_half(0); send_half(1); }
    TS(28);

    if (wg == 0) {
        asm volatile("setmaxnreg.dec.sync.aligned.u32 24;");
        const int warp = __shfl_sync(0xffffffffu, threadIdx.x >> 5, 0);
        if (warp == 0) {
            if (gemm) {
                int st = five ? 6 : 0; uint32_t ph = 0;
                const int nst = five ? 7 : 9; const uint32_t sb = five ? 10240 : 8192;
#pragma unroll 1
                for (int ks = nst; ks < 36; ks++) {
                    const int i = ks - nst;
                    if ((i % 3) == 0 && i < 21) send_half(2 + i / 3);
                    mbar_wait(BAR_EMPTYW + 8 * st, ph);
                    tma3d(B_OFF + st * sb, five ? &p.wq5 : &p.wq4, ks * 16, (216 * cta_j()) >> 6, BAR_FULLW + 8 * st, sb);
                    if (++st == nst) { st = 0; ph ^= 1; }
                }
                st = 0; ph = 1;
                int fresh = 6;
#pragma unroll 1
                for (int q = 0; q < num_jobs(); q++) {
#pragma unroll 1
                    for (int k = 0; k < DM; k += (q < has_mini() ? (mini_w() == 1 ? 96 : 48) : 32)) {
                        if (fresh) { fresh--; mbar_wait(BAR_EMPTYW + 8 * (five ? (st == 5 ? 6 : st + 1) : (3 * st + 2) >> 1), 1); }
                        else mbar_wait(BAR_EMPTYB + 8 * st, ph);
                        tma3d(B_OFF + st * 12288, q < has_mini() ? (mini_w() == 1 ? &p.w1n : &p.w1m) : &p.w1, k, job_chunk(job_id(q)), BAR_FULLB + 8 * st, 12288);
                        if (++st == 6) { st = 0; ph ^= 1; }
                    }
                }
                if (cta_isG()) {
#pragma unroll 1
                    for (int hk = 0; hk < 162; hk++) {
                        mbar_wait(BAR_EMPTYB + 8 * st, ph);
                        if (hk < 144) tma5d(B_OFF + st * 12288, &p.w2, (hk >> 1) * 32 + (hk & 1) * 4, cta_j() * 3, BAR_FULLB + 8 * st, 12288);
                        else tma3d(B_OFF + st * 12288, &p.wo, (hk - 144) * 32, cta_j() * 3, BAR_FULLB + 8 * st, 12288);
                        if (++st == 6) { st = 0; ph ^= 1; }
                    }
                }
            }
        } else if (warp == 1) {
            if (gemm) {
                const unsigned tag = get_tag();
                bar_sync(10, 288);
                if (lane < 3) atomicMax(&g_bound[(3 * cta_j() + lane) * 16], ((unsigned long long)tag << 32) | lds32(BMAX_OFF + 4 * lane));
                __syncwarp();
                if (lane == 0) red_release(&g_qkvcnt, 1);
                __syncwarp();
#pragma unroll 1
                for (int q = 0; q < num_jobs(); q++) {
                    bar_sync(job_bar(q), 160);
                    if (lane < (q < has_mini() ? mini_w() : 1)) st_release(&g_hflag[cta_m() * 32 + job_id(q) + lane], tag);
                    __syncwarp();
                }
            }
        } else if (warp == 3) {
            if (cta_isG()) {
                int sa = 0, dep = 0, next_dep = 0; uint32_t pa = 0;
#pragma unroll 1
                for (int kk = 0; kk < 84; kk++) {
                    if (kk == next_dep) {
                        mbar_wait(BAR_DEP + 8 * dep, 0);
                        dep++;
                        next_dep = kk < 63 ? (kk == 0 ? 30 : (kk == 30 ? 54 : 63)) : (kk == 63 ? 75 : kk + 1);
                    }
                    mbar_wait(BAR_EMPTYA + 8 * sa, pa);
                    if (kk >= 72 && kk < 75) tma2d(A_OFF + sa * 16384, &p.x, (3 * cta_j() + kk - 72) * 64, cta_m() * 128, BAR_FULLA + 8 * sa, 16384);
                    else bulk_load(A_OFF + sa * 16384, kk < 72 ? g_h + (size_t)(cta_m() * 72 + kk) * 16384 : g_o + (size_t)(cta_m() * 9 + (kk - 75)) * 16384, 16384, BAR_FULLA + 8 * sa, 16384);
                    if (++sa == 9) { sa = 0; pa ^= 1; }
                }
            } else {
                const unsigned tag = get_tag();
                task_table(lane);
                if (gemm) mbar_wait(BAR_WDONE, 0);
                flag_wait(&g_qkvcnt, tag * 128);
                __syncwarp();
                const float bn = lane < 24 ? __uint_as_float((uint32_t)ld_tagged(&g_bound[lane * 16])) * 1.02f : 0.f;
                asm volatile("fence.proxy.async.global;" ::: "memory");
                const float bk = __shfl_sync(0xffffffffu, bn, (lane & 7) + 8), bv = __shfl_sync(0xffffffffu, bn, (lane & 7) + 16);
                const uint32_t fastmask = __ballot_sync(0xffffffffu, __fsqrt_rn(bn * bk) + 0.5f * __log2f(fmaxf(bv, 1.0f)) <= GUARD);
                asm volatile("st.shared.u32 [%0], %1;" :: "r"(cl(FAST_OFF)), "r"(fastmask) : "memory");
                __syncwarp();
#pragma unroll 1
                for (int s = 0; s < 8; s++) {
                    if (gemm) mbar_wait(BAR_EMPTYA + 8 * (s == 0 ? 7 : 8), 0);
                    kv_load(s);
                }
            }
        } else {
            if (gemm) l2_prefetch((const uint8_t*)p.w1p + blockIdx.x * 41472, 41472, 300);
            else {
                asm volatile("nanosleep.u32 4000;");
#pragma unroll 1
                for (int i = 0; i < 36; i++) {
                    if (i < 32) l2_prefetch_bulk((const uint8_t*)p.w2p + (i * 4 + (blockIdx.x - 128)) * 41472, 41472);
                    else l2_prefetch_bulk((const uint8_t*)p.wop + ((i - 32) * 4 + (blockIdx.x - 128)) * 41472, 41472);
                }
            }
            if (cta_isG()) {
                const unsigned tag = get_tag();
                mbar_wait(BAR_WDONE, 0);
#pragma unroll 1
                for (int d = 0; d < 4; d++) {
                    if (lane < (d == 0 ? 14 : 19 + 3 * d)) flag_wait(&g_hflag[cta_m() * 32 + lane], tag);
                    __syncwarp();
                    fence_async();
                    if (lane == 0) mbar_arrive(BAR_DEP + 8 * d);
                }
                int d = 0, n = 0;
                const unsigned* f0 = &g_oflag[(cta_m() * 2) * 32 + lane];
#pragma unroll 1
                while (d < 9) {
                    unsigned a, b;
                    asm volatile("ld.acquire.gpu.global.u32 %0, [%1];" : "=r"(a) : "l"(f0) : "memory");
                    asm volatile("ld.acquire.gpu.global.u32 %0, [%1];" : "=r"(b) : "l"(f0 + 32) : "memory");
                    const uint32_t miss = ~__ballot_sync(0xffffffffu, a == tag && b == tag);
                    const int ready = miss ? ((__ffs(miss) - 1) * 18) >> 6 : 9;
                    if (ready > d) {
                        asm volatile("fence.proxy.async.global;" ::: "memory");
                        if (lane >= d && lane < ready) mbar_arrive(BAR_DEP + 8 * (4 + lane));
                        d = ready;
                    } else asm volatile("{\n.reg .pred q;\nnanosleep.u32 %1;\nsetp.gt.u32 q, %0, 4000000;\n@q trap;\n}" :: "r"(++n), "r"(d < 5 ? 500 : 20));
                }
            }
        }
        if (cta_isG()) {
            bar_sync(4, 128);
            if (elect) red_relaxed(&g_done, 1);
            return;
        }
        bar_sync(2, 256);
        asm volatile("setmaxnreg.inc.sync.aligned.u32 128;");
    } else if (wg == 3) {
        asm volatile("setmaxnreg.dec.sync.aligned.u32 24;");
        if (gemm) {
            const int tid = threadIdx.x & 127;
#pragma unroll 2
            for (int w = tid; w < 1024; w += 128) {
                uint32_t bw, bdst;
                if (w < 768) {
                    const int c = w >> 8, r = (w >> 5) & 7, k = w & 31;
                    bw = (r < num_jobs() && (r >= has_mini() || c < mini_w())) ? __ldg((const uint32_t*)p.b1p + (job_chunk(job_id(r)) + c) * 32 + k) : 0u;
                    if (r == 5 && cta_isG()) bw = __ldg((const uint32_t*)p.b2p + (3 * cta_j() + c) * 32 + k);
                    bdst = BIAS_OFF + c * 1024 + r * 128 + (((k >> 2) ^ r) << 4) + (k & 3) * 4;
                } else {
                    const int u = w - 768, q = u >> 5, k = u & 3;
                    bw = (q < 6 && k == (q >> 1)) ? (q == 5 ? 0x40000000u : ((q & 1) ? 0x3f800000u : 0x00003f80u)) : 0u;
                    bdst = ONE_OFF + u * 4;
                }
                asm volatile("st.shared.u32 [%0], %1;" :: "r"(cl(bdst)), "r"(bw) : "memory");
            }
            asm volatile("fence.proxy.async.shared::cta;" ::: "memory");
            bar_sync(7, 128);
            if (elect) mbar_arrive(BAR_INFO);
        }
        if (cta_isG()) {
            if (elect) red_relaxed(&g_done, 1);
            return;
        }
        bar_sync(1, 256);
        asm volatile("setmaxnreg.inc.sync.aligned.u32 128;");
    } else {
        const int warp = __shfl_sync(0xffffffffu, (threadIdx.x >> 5) & 3, 0), g = lane >> 2, t = lane & 3;
        asm volatile("setmaxnreg.inc.sync.aligned.u32 232;");
        if (gemm) {
            uint32_t vv[54];
            switch (cta_j()) {
                case 0: qkv_mainloop<0>(vv, wg, elect); break;
                case 1: qkv_mainloop<1>(vv, wg, elect); break;
                case 2: qkv_mainloop<2>(vv, wg, elect); break;
                case 3: qkv_mainloop<3>(vv, wg, elect); break;
                case 4: qkv_mainloop<4>(vv, wg, elect); break;
                case 5: qkv_mainloop<5>(vv, wg, elect); break;
                case 6: qkv_mainloop<6>(vv, wg, elect); break;
                default: qkv_mainloop<7>(vv, wg, elect); break;
            }
            if (wg == 1) TS(26);
            float acc0[96], acc1[96];
            kill<96>(acc0); kill<96>(acc1);
            mbar_wait(BAR_INFO, 0);
            mbar_wait(BAR_WDONE, 0);
            keep<54>(vv);
            if (wg == 1 && has_mini()) { if (mini_w() == 1) mini_mainloop<1>(acc0, acc1, elect); else mini_mainloop<2>(acc0, acc1, elect); TS(17); }
            keep<54>(vv);
            epilogue_qkv(vv, cta_m() * 16 + (wg - 1) * 8 + warp * 2, g, t, wg);
            if (wg == 1 && !has_mini()) bar_arrive(14, 256);
            TS(wg == 1 ? 27 : 30);
            bar_arrive(10, 288);
#pragma unroll 1
            for (int q = wg - 1; q < num_jobs() + cta_isG(); q += 2) {
                const bool g2 = q == num_jobs();
                const uint32_t xa = A_OFF + (warp * 16 + (lane & 15)) * 128 + (((lane >> 4) ^ (lane & 7)) << 4);
                if (g2) TS2(9);
                if (q >= has_mini()) job_mainloop(acc0, acc1, q, g2, xa, elect);
                if (g2) {
                    TS2(12);
#pragma unroll
                    for (int c = 0; c < 3; c++) {
#pragma unroll
                        for (int i2 = 4 * c; i2 < 4 * c + 4; i2++) {
#pragma unroll
                            for (int mh = 0; mh < 2; mh++) {
                                const float* a = (mh ? acc1 : acc0) + 8 * i2;
                                asm volatile("stmatrix.sync.aligned.m8n8.x4.shared.b16 [%0], {%1,%2,%3,%4};"
                                    :: "r"(cl((xa ^ ((i2 & 3) << 5)) + (3 + c) * 16384 + mh * 8192)),
                                       "r"(pack_bf16(a[0], a[1])), "r"(pack_bf16(a[2], a[3])), "r"(pack_bf16(a[4], a[5])), "r"(pack_bf16(a[6], a[7])) : "memory");
                            }
                        }
                        asm volatile("fence.proxy.async.shared::cta;" ::: "memory");
                        bar_sync(4 + wg, 128);
                        if (elect) asm volatile("cp.async.bulk.tensor.2d.global.shared::cta.bulk_group [%0, {%1, %2}], [%3];"
                                        :: "l"(&p.outm), "r"(cta_j() * 192 + c * 64), "r"(cta_m() * 128), "r"(cl(A_OFF + (3 + c) * 16384)) : "memory");
                    }
                    if (elect) asm volatile("cp.async.bulk.commit_group;\ncp.async.bulk.wait_group.read 0;" ::: "memory");
                    TS2(14);
                    break;
                }
                if (q >= has_mini()) TS(17 + (q < 4 ? q : 4));
                job_epilogue(acc0, acc1, q, warp, g, t);
                TS(22 + (q < 3 ? q : 3));
            }
        }
        if (cta_isG()) {
            bar_sync(4 + wg, 128);
            if (elect) red_relaxed(&g_done, 1);
            return;
        }
        asm volatile("setmaxnreg.dec.sync.aligned.u32 128;");
        bar_arrive(has_mini() ? 3 - wg : wg, 256);
    }
    __syncwarp();
    TS2(8 + wg);
    attention(wg, get_tag());
    TS2(12 + wg);
    bar_sync(4 + wg, 128);
    if (elect) red_relaxed(&g_done, 1);
}

typedef CUresult (*EncFn)(CUtensorMap*, CUtensorMapDataType, cuuint32_t, void*, const cuuint64_t*, const cuuint64_t*, const cuuint32_t*,
                          const cuuint32_t*, CUtensorMapInterleave, CUtensorMapSwizzle, CUtensorMapL2promotion, CUtensorMapFloatOOBfill);

void make_map(EncFn enc, CUtensorMap* m, const void* ptr, int rank, const cuuint64_t* dims, const cuuint64_t* strides, const cuuint32_t* box) {
    cuuint32_t es[5] = {1, 1, 1, 1, 1};
    enc(m, CU_TENSOR_MAP_DATA_TYPE_BFLOAT16, rank, const_cast<void*>(ptr), dims, strides, box, es, CU_TENSOR_MAP_INTERLEAVE_NONE,
        CU_TENSOR_MAP_SWIZZLE_128B, L2PROMO, CU_TENSOR_MAP_FLOAT_OOB_FILL_NONE);
}
void make_act_map(EncFn enc, CUtensorMap* m, const void* ptr, int cols) {
    cuuint64_t d[2] = {(cuuint64_t)cols, SEQ}, s[1] = {(cuuint64_t)cols * 2}; cuuint32_t b[2] = {64, 128};
    make_map(enc, m, ptr, 2, d, s, b);
}

}

extern "C" void kernel_launch(void* const* d_in, const int* in_sizes, int n_in, void* d_out, int out_size) {
    static Params prm;
    static bool ready = false;
    static const void* key[9];
    bool same = ready && key[8] == d_out;
    for (int i = 0; i < 8 && same; i++) same = key[i] == d_in[i];
    if (!same) {
        EncFn enc = nullptr; cudaDriverEntryPointQueryResult qr;
        cudaGetDriverEntryPoint("cuTensorMapEncodeTiled", (void**)&enc, cudaEnableDefault, &qr);
        make_act_map(enc, &prm.outm, d_out, DM);
        make_act_map(enc, &prm.x, d_in[0], DM);
        {
            cuuint64_t d[3] = {64, DM, 27}, s[2] = {1728 * 2, 128}; cuuint32_t b4[3] = {64, 16, 4}, b5[3] = {64, 16, 5};
            make_map(enc, &prm.wq4, d_in[1], 3, d, s, b4);
            make_map(enc, &prm.wq5, d_in[1], 3, d, s, b5);
        }
        {
            cuuint64_t d[3] = {64, DM, FF / 64}, s[2] = {FF * 2, 128}; cuuint32_t b[3] = {64, 32, 3};
            make_map(enc, &prm.w1, d_in[4], 3, d, s, b);
            cuuint32_t bn[3] = {64, 96, 1};
            make_map(enc, &prm.w1n, d_in[4], 3, d, s, bn);
            cuuint32_t bm[3] = {64, 48, 2};
            make_map(enc, &prm.w1m, d_in[4], 3, d, s, bm);
        }
        {
            cuuint64_t d[3] = {64, DM, DM / 64}, s[2] = {DM * 2, 128}; cuuint32_t b[3] = {64, 32, 3};
            make_map(enc, &prm.wo, d_in[2], 3, d, s, b);
        }
        {
            cuuint64_t d[5] = {64, 2, 4, 2280, DM / 64}, s[4] = {DM * 2, 16 * DM * 2, 2 * DM * 2, 128}; cuuint32_t b[5] = {64, 2, 4, 4, 3};
            make_map(enc, &prm.w2, d_in[6], 5, d, s, b);
        }
        prm.xp = (const __nv_bfloat16*)d_in[0]; prm.wqkvp = (const __nv_bfloat16*)d_in[1]; prm.w1p = (const __nv_bfloat16*)d_in[4];
        prm.b1p = (const __nv_bfloat16*)d_in[5]; prm.b2p = (const __nv_bfloat16*)d_in[7]; prm.out = (__nv_bfloat16*)d_out;
        prm.w2p = (const __nv_bfloat16*)d_in[6]; prm.wop = (const __nv_bfloat16*)d_in[2];
        cudaFuncSetAttribute(fused_kernel, cudaFuncAttributeMaxDynamicSharedMemorySize, SMEM_BYTES);
        for (int i = 0; i < 8; i++) key[i] = d_in[i];
        key[8] = d_out; ready = true;
    }
    fused_kernel<<<NCTA, NTHREADS, SMEM_BYTES, cudaStreamPerThread>>>(prm);
}
```

```cpp
#include <cuda_runtime.h>
#include <cuda_bf16.h>
#include <cuda.h>
#include <stdint.h>

#define L2PROMO CU_TENSOR_MAP_L2_PROMOTION_L2_128B
namespace {

constexpr int SEQ = 2048, DM = 576, FF = 4608, NH = 32;
constexpr int NCTA = 132, NTHREADS = 512, NACTA = 84;
#define GUARD 80.0f
#define HELP2 5
#define PF2NS 500
#define KVLAG 5
#define PMASK 0xAD6Bu
constexpr uint32_t POLYMASK = PMASK;

constexpr uint32_t SB = 0x400;
constexpr uint32_t A_OFF = SB;
constexpr uint32_t B_OFF = SB + 9 * 16384;
constexpr uint32_t Q_OFF = SB, Q2_OFF = SB + 12288 + 8 * 24576;
constexpr uint32_t K_OFF = SB + 12288, V_OFF = K_OFF + 8 * 12288;
constexpr uint32_t BAR_OFF = B_OFF + 6 * 12288;
constexpr uint32_t BAR_FULLA = BAR_OFF, BAR_EMPTYA = BAR_FULLA + 72, BAR_FULLB = BAR_EMPTYA + 72, BAR_EMPTYB = BAR_FULLB + 48,
                   BAR_FULLKV = BAR_EMPTYB + 48, BAR_EMPTYKV = BAR_FULLKV + 64, BAR_FULLW = BAR_EMPTYKV + 64, BAR_EMPTYW = BAR_FULLW + 72,
                   BAR_INFO = BAR_EMPTYW + 72, BAR_DEP = BAR_INFO + 16, BAR_WDONE = BAR_DEP + 13 * 8, FAST_OFF = BAR_WDONE + 8, BMAX_OFF = FAST_OFF + 4;
constexpr int NBARS = 9 + 9 + 6 + 6 + 8 + 8 + 9 + 9 + 2 + 13 + 1;
static_assert(NBARS % 16 == 0, "barrier init");
constexpr uint32_t ONE_OFF = BAR_OFF + 768;
constexpr uint32_t BIAS_OFF = BAR_OFF + 2048;
constexpr uint32_t TASK_OFF = BIAS_OFF + 3072;
constexpr uint32_t SMEM_END = TASK_OFF + 256;
static_assert(ONE_OFF + 1024 <= BIAS_OFF && BIAS_OFF % 1024 == 0, "smem map");
constexpr uint32_t SMEM_BYTES = SMEM_END - SB;
static_assert(SMEM_BYTES <= 232448, "smem");

__device__ __align__(1024) uint8_t g_h[SEQ * FF * 2];
__device__ __align__(1024) uint8_t g_o[SEQ * DM * 2];
__device__ __align__(1024) uint8_t g_qkv[96 * 98304];
__device__ unsigned long long g_bound[24 * 16];
__device__ unsigned g_done;
__device__ unsigned g_qkvcnt;
__device__ unsigned g_hflag[16 * 32];
#define XS 6
__device__ __align__(16) float4 g_part[4 * XS * 4 * 512];
__device__ unsigned g_pflag[4 * 4 * 8];
__device__ unsigned g_oflag[32 * 32];
#define TS(i)
#define TS2(i)

struct Params {
    const __nv_bfloat16* xp; const __nv_bfloat16* wqkvp; const __nv_bfloat16* w1p; const __nv_bfloat16* b1p; const __nv_bfloat16* b2p;
    const __nv_bfloat16* w2p; const __nv_bfloat16* wop;
    __nv_bfloat16* out;
    CUtensorMap wq4, wq5, w1n, w1m, w1, w2, wo, x, outm;
};

template<int N> __device__ __forceinline__ void mma_ssp(float* d, uint64_t da, uint64_t db, int sd);
template<> __device__ __forceinline__ void mma_ssp<8>(float* d, uint64_t da, uint64_t db, int sd) {
    asm volatile("{\n.reg .pred p;\nsetp.ne.b32 p, %6, 0;\nwgmma.mma_async.sync.aligned.m64n8k16.f32.bf16.bf16 {%0,%1,%2,%3}, %4, %5, p, 1, 1, 0, 1;\n}\n"
      : "+f"(d[0]),"+f"(d[1]),"+f"(d[2]),"+f"(d[3])
      : "l"(da), "l"(db), "r"(sd));
}
template<> __device__ __forceinline__ void mma_ssp<16>(float* d, uint64_t da, uint64_t db, int sd) {
    asm volatile("{\n.reg .pred p;\nsetp.ne.b32 p, %10, 0;\nwgmma.mma_async.sync.aligned.m64n16k16.f32.bf16.bf16 {%0,%1,%2,%3,%4,%5,%6,%7}, %8, %9, p, 1, 1, 0, 1;\n}\n"
      : "+f"(d[0]),"+f"(d[1]),"+f"(d[2]),"+f"(d[3]),"+f"(d[4]),"+f"(d[5]),"+f"(d[6]),"+f"(d[7])
      : "l"(da), "l"(db), "r"(sd));
}
template<> __device__ __forceinline__ void mma_ssp<24>(float* d, uint64_t da, uint64_t db, int sd) {
    asm volatile("{\n.reg .pred p;\nsetp.ne.b32 p, %14, 0;\nwgmma.mma_async.sync.aligned.m64n24k16.f32.bf16.bf16 {%0,%1,%2,%3,%4,%5,%6,%7,%8,%9,%10,%11}, %12, %13, p, 1, 1, 0, 1;\n}\n"
      : "+f"(d[0]),"+f"(d[1]),"+f"(d[2]),"+f"(d[3]),"+f"(d[4]),"+f"(d[5]),"+f"(d[6]),"+f"(d[7]),"+f"(d[8]),"+f"(d[9]),"+f"(d[10]),"+f"(d[11])
      : "l"(da), "l"(db), "r"(sd));
}
template<> __device__ __forceinline__ void mma_ssp<32>(float* d, uint64_t da, uint64_t db, int sd) {
    asm volatile("{\n.reg .pred p;\nsetp.ne.b32 p, %18, 0;\nwgmma.mma_async.sync.aligned.m64n32k16.f32.bf16.bf16 {%0,%1,%2,%3,%4,%5,%6,%7,%8,%9,%10,%11,%12,%13,%14,%15}, %16, %17, p, 1, 1, 0, 1;\n}\n"
      : "+f"(d[0]),"+f"(d[1]),"+f"(d[2]),"+f"(d[3]),"+f"(d[4]),"+f"(d[5]),"+f"(d[6]),"+f"(d[7]),"+f"(d[8]),"+f"(d[9]),"+f"(d[10]),"+f"(d[11]),"+f"(d[12]),"+f"(d[13]),"+f"(d[14]),"+f"(d[15])
      : "l"(da), "l"(db), "r"(sd));
}
template<> __device__ __forceinline__ void mma_ssp<40>(float* d, uint64_t da, uint64_t db, int sd) {
    asm volatile("{\n.reg .pred p;\nsetp.ne.b32 p, %22, 0;\nwgmma.mma_async.sync.aligned.m64n40k16.f32.bf16.bf16 {%0,%1,%2,%3,%4,%5,%6,%7,%8,%9,%10,%11,%12,%13,%14,%15,%16,%17,%18,%19}, %20, %21, p, 1, 1, 0, 1;\n}\n"
      : "+f"(d[0]),"+f"(d[1]),"+f"(d[2]),"+f"(d[3]),"+f"(d[4]),"+f"(d[5]),"+f"(d[6]),"+f"(d[7]),"+f"(d[8]),"+f"(d[9]),"+f"(d[10]),"+f"(d[11]),"+f"(d[12]),"+f"(d[13]),"+f"(d[14]),"+f"(d[15]),"+f"(d[16]),"+f"(d[17]),"+f"(d[18]),"+f"(d[19])
      : "l"(da), "l"(db), "r"(sd));
}
template<> __device__ __forceinline__ void mma_ssp<48>(float* d, uint64_t da, uint64_t db, int sd) {
    asm volatile("{\n.reg .pred p;\nsetp.ne.b32 p, %26, 0;\nwgmma.mma_async.sync.aligned.m64n48k16.f32.bf16.bf16 {%0,%1,%2,%3,%4,%5,%6,%7,%8,%9,%10,%11,%12,%13,%14,%15,%16,%17,%18,%19,%20,%21,%22,%23}, %24, %25, p, 1, 1, 0, 1;\n}\n"
      : "+f"(d[0]),"+f"(d[1]),"+f"(d[2]),"+f"(d[3]),"+f"(d[4]),"+f"(d[5]),"+f"(d[6]),"+f"(d[7]),"+f"(d[8]),"+f"(d[9]),"+f"(d[10]),"+f"(d[11]),"+f"(d[12]),"+f"(d[13]),"+f"(d[14]),"+f"(d[15]),"+f"(d[16]),"+f"(d[17]),"+f"(d[18]),"+f"(d[19]),"+f"(d[20]),"+f"(d[21]),"+f"(d[22]),"+f"(d[23])
      : "l"(da), "l"(db), "r"(sd));
}
template<> __device__ __forceinline__ void mma_ssp<56>(float* d, uint64_t da, uint64_t db, int sd) {
    asm volatile("{\n.reg .pred p;\nsetp.ne.b32 p, %30, 0;\nwgmma.mma_async.sync.aligned.m64n56k16.f32.bf16.bf16 {%0,%1,%2,%3,%4,%5,%6,%7,%8,%9,%10,%11,%12,%13,%14,%15,%16,%17,%18,%19,%20,%21,%22,%23,%24,%25,%26,%27}, %28, %29, p, 1, 1, 0, 1;\n}\n"
      : "+f"(d[0]),"+f"(d[1]),"+f"(d[2]),"+f"(d[3]),"+f"(d[4]),"+f"(d[5]),"+f"(d[6]),"+f"(d[7]),"+f"(d[8]),"+f"(d[9]),"+f"(d[10]),"+f"(d[11]),"+f"(d[12]),"+f"(d[13]),"+f"(d[14]),"+f"(d[15]),"+f"(d[16]),"+f"(d[17]),"+f"(d[18]),"+f"(d[19]),"+f"(d[20]),"+f"(d[21]),"+f"(d[22]),"+f"(d[23]),"+f"(d[24]),"+f"(d[25]),"+f"(d[26]),"+f"(d[27])
      : "l"(da), "l"(db), "r"(sd));
}
template<> __device__ __forceinline__ void mma_ssp<64>(float* d, uint64_t da, uint64_t db, int sd) {
    asm volatile("{\n.reg .pred p;\nsetp.ne.b32 p, %34, 0;\nwgmma.mma_async.sync.aligned.m64n64k16.f32.bf16.bf16 {%0,%1,%2,%3,%4,%5,%6,%7,%8,%9,%10,%11,%12,%13,%14,%15,%16,%17,%18,%19,%20,%21,%22,%23,%24,%25,%26,%27,%28,%29,%30,%31}, %32, %33, p, 1, 1, 0, 1;\n}\n"
      : "+f"(d[0]),"+f"(d[1]),"+f"(d[2]),"+f"(d[3]),"+f"(d[4]),"+f"(d[5]),"+f"(d[6]),"+f"(d[7]),"+f"(d[8]),"+f"(d[9]),"+f"(d[10]),"+f"(d[11]),"+f"(d[12]),"+f"(d[13]),"+f"(d[14]),"+f"(d[15]),"+f"(d[16]),"+f"(d[17]),"+f"(d[18]),"+f"(d[19]),"+f"(d[20]),"+f"(d[21]),"+f"(d[22]),"+f"(d[23]),"+f"(d[24]),"+f"(d[25]),"+f"(d[26]),"+f"(d[27]),"+f"(d[28]),"+f"(d[29]),"+f"(d[30]),"+f"(d[31])
      : "l"(da), "l"(db), "r"(sd));
}
template<> __device__ __forceinline__ void mma_ssp<80>(float* d, uint64_t da, uint64_t db, int sd) {
    asm volatile("{\n.reg .pred p;\nsetp.ne.b32 p, %42, 0;\nwgmma.mma_async.sync.aligned.m64n80k16.f32.bf16.bf16 {%0,%1,%2,%3,%4,%5,%6,%7,%8,%9,%10,%11,%12,%13,%14,%15,%16,%17,%18,%19,%20,%21,%22,%23,%24,%25,%26,%27,%28,%29,%30,%31,%32,%33,%34,%35,%36,%37,%38,%39}, %40, %41, p, 1, 1, 0, 1;\n}\n"
      : "+f"(d[0]),"+f"(d[1]),"+f"(d[2]),"+f"(d[3]),"+f"(d[4]),"+f"(d[5]),"+f"(d[6]),"+f"(d[7]),"+f"(d[8]),"+f"(d[9]),"+f"(d[10]),"+f"(d[11]),"+f"(d[12]),"+f"(d[13]),"+f"(d[14]),"+f"(d[15]),"+f"(d[16]),"+f"(d[17]),"+f"(d[18]),"+f"(d[19]),"+f"(d[20]),"+f"(d[21]),"+f"(d[22]),"+f"(d[23]),"+f"(d[24]),"+f"(d[25]),"+f"(d[26]),"+f"(d[27]),"+f"(d[28]),"+f"(d[29]),"+f"(d[30]),"+f"(d[31]),"+f"(d[32]),"+f"(d[33]),"+f"(d[34]),"+f"(d[35]),"+f"(d[36]),"+f"(d[37]),"+f"(d[38]),"+f"(d[39])
      : "l"(da), "l"(db), "r"(sd));
}
template<> __device__ __forceinline__ void mma_ssp<128>(float* d, uint64_t da, uint64_t db, int sd) {
    asm volatile("{\n.reg .pred p;\nsetp.ne.b32 p, %66, 0;\nwgmma.mma_async.sync.aligned.m64n128k16.f32.bf16.bf16 {%0,%1,%2,%3,%4,%5,%6,%7,%8,%9,%10,%11,%12,%13,%14,%15,%16,%17,%18,%19,%20,%21,%22,%23,%24,%25,%26,%27,%28,%29,%30,%31,%32,%33,%34,%35,%36,%37,%38,%39,%40,%41,%42,%43,%44,%45,%46,%47,%48,%49,%50,%51,%52,%53,%54,%55,%56,%57,%58,%59,%60,%61,%62,%63}, %64, %65, p, 1, 1, 0, 1;\n}\n"
      : "+f"(d[0]),"+f"(d[1]),"+f"(d[2]),"+f"(d[3]),"+f"(d[4]),"+f"(d[5]),"+f"(d[6]),"+f"(d[7]),"+f"(d[8]),"+f"(d[9]),"+f"(d[10]),"+f"(d[11]),"+f"(d[12]),"+f"(d[13]),"+f"(d[14]),"+f"(d[15]),"+f"(d[16]),"+f"(d[17]),"+f"(d[18]),"+f"(d[19]),"+f"(d[20]),"+f"(d[21]),"+f"(d[22]),"+f"(d[23]),"+f"(d[24]),"+f"(d[25]),"+f"(d[26]),"+f"(d[27]),"+f"(d[28]),"+f"(d[29]),"+f"(d[30]),"+f"(d[31]),"+f"(d[32]),"+f"(d[33]),"+f"(d[34]),"+f"(d[35]),"+f"(d[36]),"+f"(d[37]),"+f"(d[38]),"+f"(d[39]),"+f"(d[40]),"+f"(d[41]),"+f"(d[42]),"+f"(d[43]),"+f"(d[44]),"+f"(d[45]),"+f"(d[46]),"+f"(d[47]),"+f"(d[48]),"+f"(d[49]),"+f"(d[50]),"+f"(d[51]),"+f"(d[52]),"+f"(d[53]),"+f"(d[54]),"+f"(d[55]),"+f"(d[56]),"+f"(d[57]),"+f"(d[58]),"+f"(d[59]),"+f"(d[60]),"+f"(d[61]),"+f"(d[62]),"+f"(d[63])
      : "l"(da), "l"(db), "r"(sd));
}
template<> __device__ __forceinline__ void mma_ssp<152>(float* d, uint64_t da, uint64_t db, int sd) {
    asm volatile("{\n.reg .pred p;\nsetp.ne.b32 p, %78, 0;\nwgmma.mma_async.sync.aligned.m64n152k16.f32.bf16.bf16 {%0,%1,%2,%3,%4,%5,%6,%7,%8,%9,%10,%11,%12,%13,%14,%15,%16,%17,%18,%19,%20,%21,%22,%23,%24,%25,%26,%27,%28,%29,%30,%31,%32,%33,%34,%35,%36,%37,%38,%39,%40,%41,%42,%43,%44,%45,%46,%47,%48,%49,%50,%51,%52,%53,%54,%55,%56,%57,%58,%59,%60,%61,%62,%63,%64,%65,%66,%67,%68,%69,%70,%71,%72,%73,%74,%75}, %76, %77, p, 1, 1, 0, 1;\n}\n"
      : "+f"(d[0]),"+f"(d[1]),"+f"(d[2]),"+f"(d[3]),"+f"(d[4]),"+f"(d[5]),"+f"(d[6]),"+f"(d[7]),"+f"(d[8]),"+f"(d[9]),"+f"(d[10]),"+f"(d[11]),"+f"(d[12]),"+f"(d[13]),"+f"(d[14]),"+f"(d[15]),"+f"(d[16]),"+f"(d[17]),"+f"(d[18]),"+f"(d[19]),"+f"(d[20]),"+f"(d[21]),"+f"(d[22]),"+f"(d[23]),"+f"(d[24]),"+f"(d[25]),"+f"(d[26]),"+f"(d[27]),"+f"(d[28]),"+f"(d[29]),"+f"(d[30]),"+f"(d[31]),"+f"(d[32]),"+f"(d[33]),"+f"(d[34]),"+f"(d[35]),"+f"(d[36]),"+f"(d[37]),"+f"(d[38]),"+f"(d[39]),"+f"(d[40]),"+f"(d[41]),"+f"(d[42]),"+f"(d[43]),"+f"(d[44]),"+f"(d[45]),"+f"(d[46]),"+f"(d[47]),"+f"(d[48]),"+f"(d[49]),"+f"(d[50]),"+f"(d[51]),"+f"(d[52]),"+f"(d[53]),"+f"(d[54]),"+f"(d[55]),"+f"(d[56]),"+f"(d[57]),"+f"(d[58]),"+f"(d[59]),"+f"(d[60]),"+f"(d[61]),"+f"(d[62]),"+f"(d[63]),"+f"(d[64]),"+f"(d[65]),"+f"(d[66]),"+f"(d[67]),"+f"(d[68]),"+f"(d[69]),"+f"(d[70]),"+f"(d[71]),"+f"(d[72]),"+f"(d[73]),"+f"(d[74]),"+f"(d[75])
      : "l"(da), "l"(db), "r"(sd));
}
template<> __device__ __forceinline__ void mma_ssp<160>(float* d, uint64_t da, uint64_t db, int sd) {
    asm volatile("{\n.reg .pred p;\nsetp.ne.b32 p, %82, 0;\nwgmma.mma_async.sync.aligned.m64n160k16.f32.bf16.bf16 {%0,%1,%2,%3,%4,%5,%6,%7,%8,%9,%10,%11,%12,%13,%14,%15,%16,%17,%18,%19,%20,%21,%22,%23,%24,%25,%26,%27,%28,%29,%30,%31,%32,%33,%34,%35,%36,%37,%38,%39,%40,%41,%42,%43,%44,%45,%46,%47,%48,%49,%50,%51,%52,%53,%54,%55,%56,%57,%58,%59,%60,%61,%62,%63,%64,%65,%66,%67,%68,%69,%70,%71,%72,%73,%74,%75,%76,%77,%78,%79}, %80, %81, p, 1, 1, 0, 1;\n}\n"
      : "+f"(d[0]),"+f"(d[1]),"+f"(d[2]),"+f"(d[3]),"+f"(d[4]),"+f"(d[5]),"+f"(d[6]),"+f"(d[7]),"+f"(d[8]),"+f"(d[9]),"+f"(d[10]),"+f"(d[11]),"+f"(d[12]),"+f"(d[13]),"+f"(d[14]),"+f"(d[15]),"+f"(d[16]),"+f"(d[17]),"+f"(d[18]),"+f"(d[19]),"+f"(d[20]),"+f"(d[21]),"+f"(d[22]),"+f"(d[23]),"+f"(d[24]),"+f"(d[25]),"+f"(d[26]),"+f"(d[27]),"+f"(d[28]),"+f"(d[29]),"+f"(d[30]),"+f"(d[31]),"+f"(d[32]),"+f"(d[33]),"+f"(d[34]),"+f"(d[35]),"+f"(d[36]),"+f"(d[37]),"+f"(d[38]),"+f"(d[39]),"+f"(d[40]),"+f"(d[41]),"+f"(d[42]),"+f"(d[43]),"+f"(d[44]),"+f"(d[45]),"+f"(d[46]),"+f"(d[47]),"+f"(d[48]),"+f"(d[49]),"+f"(d[50]),"+f"(d[51]),"+f"(d[52]),"+f"(d[53]),"+f"(d[54]),"+f"(d[55]),"+f"(d[56]),"+f"(d[57]),"+f"(d[58]),"+f"(d[59]),"+f"(d[60]),"+f"(d[61]),"+f"(d[62]),"+f"(d[63]),"+f"(d[64]),"+f"(d[65]),"+f"(d[66]),"+f"(d[67]),"+f"(d[68]),"+f"(d[69]),"+f"(d[70]),"+f"(d[71]),"+f"(d[72]),"+f"(d[73]),"+f"(d[74]),"+f"(d[75]),"+f"(d[76]),"+f"(d[77]),"+f"(d[78]),"+f"(d[79])
      : "l"(da), "l"(db), "r"(sd));
}
template<> __device__ __forceinline__ void mma_ssp<168>(float* d, uint64_t da, uint64_t db, int sd) {
    asm volatile("{\n.reg .pred p;\nsetp.ne.b32 p, %86, 0;\nwgmma.mma_async.sync.aligned.m64n168k16.f32.bf16.bf16 {%0,%1,%2,%3,%4,%5,%6,%7,%8,%9,%10,%11,%12,%13,%14,%15,%16,%17,%18,%19,%20,%21,%22,%23,%24,%25,%26,%27,%28,%29,%30,%31,%32,%33,%34,%35,%36,%37,%38,%39,%40,%41,%42,%43,%44,%45,%46,%47,%48,%49,%50,%51,%52,%53,%54,%55,%56,%57,%58,%59,%60,%61,%62,%63,%64,%65,%66,%67,%68,%69,%70,%71,%72,%73,%74,%75,%76,%77,%78,%79,%80,%81,%82,%83}, %84, %85, p, 1, 1, 0, 1;\n}\n"
      : "+f"(d[0]),"+f"(d[1]),"+f"(d[2]),"+f"(d[3]),"+f"(d[4]),"+f"(d[5]),"+f"(d[6]),"+f"(d[7]),"+f"(d[8]),"+f"(d[9]),"+f"(d[10]),"+f"(d[11]),"+f"(d[12]),"+f"(d[13]),"+f"(d[14]),"+f"(d[15]),"+f"(d[16]),"+f"(d[17]),"+f"(d[18]),"+f"(d[19]),"+f"(d[20]),"+f"(d[21]),"+f"(d[22]),"+f"(d[23]),"+f"(d[24]),"+f"(d[25]),"+f"(d[26]),"+f"(d[27]),"+f"(d[28]),"+f"(d[29]),"+f"(d[30]),"+f"(d[31]),"+f"(d[32]),"+f"(d[33]),"+f"(d[34]),"+f"(d[35]),"+f"(d[36]),"+f"(d[37]),"+f"(d[38]),"+f"(d[39]),"+f"(d[40]),"+f"(d[41]),"+f"(d[42]),"+f"(d[43]),"+f"(d[44]),"+f"(d[45]),"+f"(d[46]),"+f"(d[47]),"+f"(d[48]),"+f"(d[49]),"+f"(d[50]),"+f"(d[51]),"+f"(d[52]),"+f"(d[53]),"+f"(d[54]),"+f"(d[55]),"+f"(d[56]),"+f"(d[57]),"+f"(d[58]),"+f"(d[59]),"+f"(d[60]),"+f"(d[61]),"+f"(d[62]),"+f"(d[63]),"+f"(d[64]),"+f"(d[65]),"+f"(d[66]),"+f"(d[67]),"+f"(d[68]),"+f"(d[69]),"+f"(d[70]),"+f"(d[71]),"+f"(d[72]),"+f"(d[73]),"+f"(d[74]),"+f"(d[75]),"+f"(d[76]),"+f"(d[77]),"+f"(d[78]),"+f"(d[79]),"+f"(d[80]),"+f"(d[81]),"+f"(d[82]),"+f"(d[83])
      : "l"(da), "l"(db), "r"(sd));
}
template<> __device__ __forceinline__ void mma_ssp<176>(float* d, uint64_t da, uint64_t db, int sd) {
    asm volatile("{\n.reg .pred p;\nsetp.ne.b32 p, %90, 0;\nwgmma.mma_async.sync.aligned.m64n176k16.f32.bf16.bf16 {%0,%1,%2,%3,%4,%5,%6,%7,%8,%9,%10,%11,%12,%13,%14,%15,%16,%17,%18,%19,%20,%21,%22,%23,%24,%25,%26,%27,%28,%29,%30,%31,%32,%33,%34,%35,%36,%37,%38,%39,%40,%41,%42,%43,%44,%45,%46,%47,%48,%49,%50,%51,%52,%53,%54,%55,%56,%57,%58,%59,%60,%61,%62,%63,%64,%65,%66,%67,%68,%69,%70,%71,%72,%73,%74,%75,%76,%77,%78,%79,%80,%81,%82,%83,%84,%85,%86,%87}, %88, %89, p, 1, 1, 0, 1;\n}\n"
      : "+f"(d[0]),"+f"(d[1]),"+f"(d[2]),"+f"(d[3]),"+f"(d[4]),"+f"(d[5]),"+f"(d[6]),"+f"(d[7]),"+f"(d[8]),"+f"(d[9]),"+f"(d[10]),"+f"(d[11]),"+f"(d[12]),"+f"(d[13]),"+f"(d[14]),"+f"(d[15]),"+f"(d[16]),"+f"(d[17]),"+f"(d[18]),"+f"(d[19]),"+f"(d[20]),"+f"(d[21]),"+f"(d[22]),"+f"(d[23]),"+f"(d[24]),"+f"(d[25]),"+f"(d[26]),"+f"(d[27]),"+f"(d[28]),"+f"(d[29]),"+f"(d[30]),"+f"(d[31]),"+f"(d[32]),"+f"(d[33]),"+f"(d[34]),"+f"(d[35]),"+f"(d[36]),"+f"(d[37]),"+f"(d[38]),"+f"(d[39]),"+f"(d[40]),"+f"(d[41]),"+f"(d[42]),"+f"(d[43]),"+f"(d[44]),"+f"(d[45]),"+f"(d[46]),"+f"(d[47]),"+f"(d[48]),"+f"(d[49]),"+f"(d[50]),"+f"(d[51]),"+f"(d[52]),"+f"(d[53]),"+f"(d[54]),"+f"(d[55]),"+f"(d[56]),"+f"(d[57]),"+f"(d[58]),"+f"(d[59]),"+f"(d[60]),"+f"(d[61]),"+f"(d[62]),"+f"(d[63]),"+f"(d[64]),"+f"(d[65]),"+f"(d[66]),"+f"(d[67]),"+f"(d[68]),"+f"(d[69]),"+f"(d[70]),"+f"(d[71]),"+f"(d[72]),"+f"(d[73]),"+f"(d[74]),"+f"(d[75]),"+f"(d[76]),"+f"(d[77]),"+f"(d[78]),"+f"(d[79]),"+f"(d[80]),"+f"(d[81]),"+f"(d[82]),"+f"(d[83]),"+f"(d[84]),"+f"(d[85]),"+f"(d[86]),"+f"(d[87])
      : "l"(da), "l"(db), "r"(sd));
}
template<> __device__ __forceinline__ void mma_ssp<184>(float* d, uint64_t da, uint64_t db, int sd) {
    asm volatile("{\n.reg .pred p;\nsetp.ne.b32 p, %94, 0;\nwgmma.mma_async.sync.aligned.m64n184k16.f32.bf16.bf16 {%0,%1,%2,%3,%4,%5,%6,%7,%8,%9,%10,%11,%12,%13,%14,%15,%16,%17,%18,%19,%20,%21,%22,%23,%24,%25,%26,%27,%28,%29,%30,%31,%32,%33,%34,%35,%36,%37,%38,%39,%40,%41,%42,%43,%44,%45,%46,%47,%48,%49,%50,%51,%52,%53,%54,%55,%56,%57,%58,%59,%60,%61,%62,%63,%64,%65,%66,%67,%68,%69,%70,%71,%72,%73,%74,%75,%76,%77,%78,%79,%80,%81,%82,%83,%84,%85,%86,%87,%88,%89,%90,%91}, %92, %93, p, 1, 1, 0, 1;\n}\n"
      : "+f"(d[0]),"+f"(d[1]),"+f"(d[2]),"+f"(d[3]),"+f"(d[4]),"+f"(d[5]),"+f"(d[6]),"+f"(d[7]),"+f"(d[8]),"+f"(d[9]),"+f"(d[10]),"+f"(d[11]),"+f"(d[12]),"+f"(d[13]),"+f"(d[14]),"+f"(d[15]),"+f"(d[16]),"+f"(d[17]),"+f"(d[18]),"+f"(d[19]),"+f"(d[20]),"+f"(d[21]),"+f"(d[22]),"+f"(d[23]),"+f"(d[24]),"+f"(d[25]),"+f"(d[26]),"+f"(d[27]),"+f"(d[28]),"+f"(d[29]),"+f"(d[30]),"+f"(d[31]),"+f"(d[32]),"+f"(d[33]),"+f"(d[34]),"+f"(d[35]),"+f"(d[36]),"+f"(d[37]),"+f"(d[38]),"+f"(d[39]),"+f"(d[40]),"+f"(d[41]),"+f"(d[42]),"+f"(d[43]),"+f"(d[44]),"+f"(d[45]),"+f"(d[46]),"+f"(d[47]),"+f"(d[48]),"+f"(d[49]),"+f"(d[50]),"+f"(d[51]),"+f"(d[52]),"+f"(d[53]),"+f"(d[54]),"+f"(d[55]),"+f"(d[56]),"+f"(d[57]),"+f"(d[58]),"+f"(d[59]),"+f"(d[60]),"+f"(d[61]),"+f"(d[62]),"+f"(d[63]),"+f"(d[64]),"+f"(d[65]),"+f"(d[66]),"+f"(d[67]),"+f"(d[68]),"+f"(d[69]),"+f"(d[70]),"+f"(d[71]),"+f"(d[72]),"+f"(d[73]),"+f"(d[74]),"+f"(d[75]),"+f"(d[76]),"+f"(d[77]),"+f"(d[78]),"+f"(d[79]),"+f"(d[80]),"+f"(d[81]),"+f"(d[82]),"+f"(d[83]),"+f"(d[84]),"+f"(d[85]),"+f"(d[86]),"+f"(d[87]),"+f"(d[88]),"+f"(d[89]),"+f"(d[90]),"+f"(d[91])
      : "l"(da), "l"(db), "r"(sd));
}
template<> __device__ __forceinline__ void mma_ssp<192>(float* d, uint64_t da, uint64_t db, int sd) {
    asm volatile("{\n.reg .pred p;\nsetp.ne.b32 p, %98, 0;\nwgmma.mma_async.sync.aligned.m64n192k16.f32.bf16.bf16 {%0,%1,%2,%3,%4,%5,%6,%7,%8,%9,%10,%11,%12,%13,%14,%15,%16,%17,%18,%19,%20,%21,%22,%23,%24,%25,%26,%27,%28,%29,%30,%31,%32,%33,%34,%35,%36,%37,%38,%39,%40,%41,%42,%43,%44,%45,%46,%47,%48,%49,%50,%51,%52,%53,%54,%55,%56,%57,%58,%59,%60,%61,%62,%63,%64,%65,%66,%67,%68,%69,%70,%71,%72,%73,%74,%75,%76,%77,%78,%79,%80,%81,%82,%83,%84,%85,%86,%87,%88,%89,%90,%91,%92,%93,%94,%95}, %96, %97, p, 1, 1, 0, 1;\n}\n"
      : "+f"(d[0]),"+f"(d[1]),"+f"(d[2]),"+f"(d[3]),"+f"(d[4]),"+f"(d[5]),"+f"(d[6]),"+f"(d[7]),"+f"(d[8]),"+f"(d[9]),"+f"(d[10]),"+f"(d[11]),"+f"(d[12]),"+f"(d[13]),"+f"(d[14]),"+f"(d[15]),"+f"(d[16]),"+f"(d[17]),"+f"(d[18]),"+f"(d[19]),"+f"(d[20]),"+f"(d[21]),"+f"(d[22]),"+f"(d[23]),"+f"(d[24]),"+f"(d[25]),"+f"(d[26]),"+f"(d[27]),"+f"(d[28]),"+f"(d[29]),"+f"(d[30]),"+f"(d[31]),"+f"(d[32]),"+f"(d[33]),"+f"(d[34]),"+f"(d[35]),"+f"(d[36]),"+f"(d[37]),"+f"(d[38]),"+f"(d[39]),"+f"(d[40]),"+f"(d[41]),"+f"(d[42]),"+f"(d[43]),"+f"(d[44]),"+f"(d[45]),"+f"(d[46]),"+f"(d[47]),"+f"(d[48]),"+f"(d[49]),"+f"(d[50]),"+f"(d[51]),"+f"(d[52]),"+f"(d[53]),"+f"(d[54]),"+f"(d[55]),"+f"(d[56]),"+f"(d[57]),"+f"(d[58]),"+f"(d[59]),"+f"(d[60]),"+f"(d[61]),"+f"(d[62]),"+f"(d[63]),"+f"(d[64]),"+f"(d[65]),"+f"(d[66]),"+f"(d[67]),"+f"(d[68]),"+f"(d[69]),"+f"(d[70]),"+f"(d[71]),"+f"(d[72]),"+f"(d[73]),"+f"(d[74]),"+f"(d[75]),"+f"(d[76]),"+f"(d[77]),"+f"(d[78]),"+f"(d[79]),"+f"(d[80]),"+f"(d[81]),"+f"(d[82]),"+f"(d[83]),"+f"(d[84]),"+f"(d[85]),"+f"(d[86]),"+f"(d[87]),"+f"(d[88]),"+f"(d[89]),"+f"(d[90]),"+f"(d[91]),"+f"(d[92]),"+f"(d[93]),"+f"(d[94]),"+f"(d[95])
      : "l"(da), "l"(db), "r"(sd));
}
template<> __device__ __forceinline__ void mma_ssp<200>(float* d, uint64_t da, uint64_t db, int sd) {
    asm volatile("{\n.reg .pred p;\nsetp.ne.b32 p, %102, 0;\nwgmma.mma_async.sync.aligned.m64n200k16.f32.bf16.bf16 {%0,%1,%2,%3,%4,%5,%6,%7,%8,%9,%10,%11,%12,%13,%14,%15,%16,%17,%18,%19,%20,%21,%22,%23,%24,%25,%26,%27,%28,%29,%30,%31,%32,%33,%34,%35,%36,%37,%38,%39,%40,%41,%42,%43,%44,%45,%46,%47,%48,%49,%50,%51,%52,%53,%54,%55,%56,%57,%58,%59,%60,%61,%62,%63,%64,%65,%66,%67,%68,%69,%70,%71,%72,%73,%74,%75,%76,%77,%78,%79,%80,%81,%82,%83,%84,%85,%86,%87,%88,%89,%90,%91,%92,%93,%94,%95,%96,%97,%98,%99}, %100, %101, p, 1, 1, 0, 1;\n}\n"
      : "+f"(d[0]),"+f"(d[1]),"+f"(d[2]),"+f"(d[3]),"+f"(d[4]),"+f"(d[5]),"+f"(d[6]),"+f"(d[7]),"+f"(d[8]),"+f"(d[9]),"+f"(d[10]),"+f"(d[11]),"+f"(d[12]),"+f"(d[13]),"+f"(d[14]),"+f"(d[15]),"+f"(d[16]),"+f"(d[17]),"+f"(d[18]),"+f"(d[19]),"+f"(d[20]),"+f"(d[21]),"+f"(d[22]),"+f"(d[23]),"+f"(d[24]),"+f"(d[25]),"+f"(d[26]),"+f"(d[27]),"+f"(d[28]),"+f"(d[29]),"+f"(d[30]),"+f"(d[31]),"+f"(d[32]),"+f"(d[33]),"+f"(d[34]),"+f"(d[35]),"+f"(d[36]),"+f"(d[37]),"+f"(d[38]),"+f"(d[39]),"+f"(d[40]),"+f"(d[41]),"+f"(d[42]),"+f"(d[43]),"+f"(d[44]),"+f"(d[45]),"+f"(d[46]),"+f"(d[47]),"+f"(d[48]),"+f"(d[49]),"+f"(d[50]),"+f"(d[51]),"+f"(d[52]),"+f"(d[53]),"+f"(d[54]),"+f"(d[55]),"+f"(d[56]),"+f"(d[57]),"+f"(d[58]),"+f"(d[59]),"+f"(d[60]),"+f"(d[61]),"+f"(d[62]),"+f"(d[63]),"+f"(d[64]),"+f"(d[65]),"+f"(d[66]),"+f"(d[67]),"+f"(d[68]),"+f"(d[69]),"+f"(d[70]),"+f"(d[71]),"+f"(d[72]),"+f"(d[73]),"+f"(d[74]),"+f"(d[75]),"+f"(d[76]),"+f"(d[77]),"+f"(d[78]),"+f"(d[79]),"+f"(d[80]),"+f"(d[81]),"+f"(d[82]),"+f"(d[83]),"+f"(d[84]),"+f"(d[85]),"+f"(d[86]),"+f"(d[87]),"+f"(d[88]),"+f"(d[89]),"+f"(d[90]),"+f"(d[91]),"+f"(d[92]),"+f"(d[93]),"+f"(d[94]),"+f"(d[95]),"+f"(d[96]),"+f"(d[97]),"+f"(d[98]),"+f"(d[99])
      : "l"(da), "l"(db), "r"(sd));
}
template<int SD> __device__ __forceinline__ void mma_n192_ss(float* d, uint64_t da, uint64_t db) {
    asm volatile("wgmma.mma_async.sync.aligned.m64n192k16.f32.bf16.bf16 {%0,%1,%2,%3,%4,%5,%6,%7,%8,%9,%10,%11,%12,%13,%14,%15,%16,%17,%18,%19,%20,%21,%22,%23,%24,%25,%26,%27,%28,%29,%30,%31,%32,%33,%34,%35,%36,%37,%38,%39,%40,%41,%42,%43,%44,%45,%46,%47,%48,%49,%50,%51,%52,%53,%54,%55,%56,%57,%58,%59,%60,%61,%62,%63,%64,%65,%66,%67,%68,%69,%70,%71,%72,%73,%74,%75,%76,%77,%78,%79,%80,%81,%82,%83,%84,%85,%86,%87,%88,%89,%90,%91,%92,%93,%94,%95}, %96, %97, %98, 1, 1, 0, 1;\n"
      : "+f"(d[0]),"+f"(d[1]),"+f"(d[2]),"+f"(d[3]),"+f"(d[4]),"+f"(d[5]),"+f"(d[6]),"+f"(d[7]),"+f"(d[8]),"+f"(d[9]),"+f"(d[10]),"+f"(d[11]),"+f"(d[12]),"+f"(d[13]),"+f"(d[14]),"+f"(d[15]),"+f"(d[16]),"+f"(d[17]),"+f"(d[18]),"+f"(d[19]),"+f"(d[20]),"+f"(d[21]),"+f"(d[22]),"+f"(d[23]),"+f"(d[24]),"+f"(d[25]),"+f"(d[26]),"+f"(d[27]),"+f"(d[28]),"+f"(d[29]),"+f"(d[30]),"+f"(d[31]),"+f"(d[32]),"+f"(d[33]),"+f"(d[34]),"+f"(d[35]),"+f"(d[36]),"+f"(d[37]),"+f"(d[38]),"+f"(d[39]),"+f"(d[40]),"+f"(d[41]),"+f"(d[42]),"+f"(d[43]),"+f"(d[44]),"+f"(d[45]),"+f"(d[46]),"+f"(d[47]),"+f"(d[48]),"+f"(d[49]),"+f"(d[50]),"+f"(d[51]),"+f"(d[52]),"+f"(d[53]),"+f"(d[54]),"+f"(d[55]),"+f"(d[56]),"+f"(d[57]),"+f"(d[58]),"+f"(d[59]),"+f"(d[60]),"+f"(d[61]),"+f"(d[62]),"+f"(d[63]),"+f"(d[64]),"+f"(d[65]),"+f"(d[66]),"+f"(d[67]),"+f"(d[68]),"+f"(d[69]),"+f"(d[70]),"+f"(d[71]),"+f"(d[72]),"+f"(d[73]),"+f"(d[74]),"+f"(d[75]),"+f"(d[76]),"+f"(d[77]),"+f"(d[78]),"+f"(d[79]),"+f"(d[80]),"+f"(d[81]),"+f"(d[82]),"+f"(d[83]),"+f"(d[84]),"+f"(d[85]),"+f"(d[86]),"+f"(d[87]),"+f"(d[88]),"+f"(d[89]),"+f"(d[90]),"+f"(d[91]),"+f"(d[92]),"+f"(d[93]),"+f"(d[94]),"+f"(d[95])
      : "l"(da), "l"(db), "n"(SD));
}
template<int SD> __device__ __forceinline__ void mma_n64_ss(float* d, uint64_t da, uint64_t db) {
    asm volatile("wgmma.mma_async.sync.aligned.m64n64k16.f32.bf16.bf16 {%0,%1,%2,%3,%4,%5,%6,%7,%8,%9,%10,%11,%12,%13,%14,%15,%16,%17,%18,%19,%20,%21,%22,%23,%24,%25,%26,%27,%28,%29,%30,%31}, %32, %33, %34, 1, 1, 0, 1;\n"
      : "+f"(d[0]),"+f"(d[1]),"+f"(d[2]),"+f"(d[3]),"+f"(d[4]),"+f"(d[5]),"+f"(d[6]),"+f"(d[7]),"+f"(d[8]),"+f"(d[9]),"+f"(d[10]),"+f"(d[11]),"+f"(d[12]),"+f"(d[13]),"+f"(d[14]),"+f"(d[15]),"+f"(d[16]),"+f"(d[17]),"+f"(d[18]),"+f"(d[19]),"+f"(d[20]),"+f"(d[21]),"+f"(d[22]),"+f"(d[23]),"+f"(d[24]),"+f"(d[25]),"+f"(d[26]),"+f"(d[27]),"+f"(d[28]),"+f"(d[29]),"+f"(d[30]),"+f"(d[31])
      : "l"(da), "l"(db), "n"(SD));
}
template<int SD> __device__ __forceinline__ void mma_n128_ss(float* d, uint64_t da, uint64_t db) {
    asm volatile("wgmma.mma_async.sync.aligned.m64n128k16.f32.bf16.bf16 {%0,%1,%2,%3,%4,%5,%6,%7,%8,%9,%10,%11,%12,%13,%14,%15,%16,%17,%18,%19,%20,%21,%22,%23,%24,%25,%26,%27,%28,%29,%30,%31,%32,%33,%34,%35,%36,%37,%38,%39,%40,%41,%42,%43,%44,%45,%46,%47,%48,%49,%50,%51,%52,%53,%54,%55,%56,%57,%58,%59,%60,%61,%62,%63}, %64, %65, %66, 1, 1, 0, 1;\n"
      : "+f"(d[0]),"+f"(d[1]),"+f"(d[2]),"+f"(d[3]),"+f"(d[4]),"+f"(d[5]),"+f"(d[6]),"+f"(d[7]),"+f"(d[8]),"+f"(d[9]),"+f"(d[10]),"+f"(d[11]),"+f"(d[12]),"+f"(d[13]),"+f"(d[14]),"+f"(d[15]),"+f"(d[16]),"+f"(d[17]),"+f"(d[18]),"+f"(d[19]),"+f"(d[20]),"+f"(d[21]),"+f"(d[22]),"+f"(d[23]),"+f"(d[24]),"+f"(d[25]),"+f"(d[26]),"+f"(d[27]),"+f"(d[28]),"+f"(d[29]),"+f"(d[30]),"+f"(d[31]),"+f"(d[32]),"+f"(d[33]),"+f"(d[34]),"+f"(d[35]),"+f"(d[36]),"+f"(d[37]),"+f"(d[38]),"+f"(d[39]),"+f"(d[40]),"+f"(d[41]),"+f"(d[42]),"+f"(d[43]),"+f"(d[44]),"+f"(d[45]),"+f"(d[46]),"+f"(d[47]),"+f"(d[48]),"+f"(d[49]),"+f"(d[50]),"+f"(d[51]),"+f"(d[52]),"+f"(d[53]),"+f"(d[54]),"+f"(d[55]),"+f"(d[56]),"+f"(d[57]),"+f"(d[58]),"+f"(d[59]),"+f"(d[60]),"+f"(d[61]),"+f"(d[62]),"+f"(d[63])
      : "l"(da), "l"(db), "n"(SD));
}
template<int SD> __device__ __forceinline__ void mma_n64_rs(float* d, uint32_t a0, uint32_t a1, uint32_t a2, uint32_t a3, uint64_t db) {
    asm volatile("wgmma.mma_async.sync.aligned.m64n64k16.f32.bf16.bf16 {%0,%1,%2,%3,%4,%5,%6,%7,%8,%9,%10,%11,%12,%13,%14,%15,%16,%17,%18,%19,%20,%21,%22,%23,%24,%25,%26,%27,%28,%29,%30,%31}, {%32,%33,%34,%35}, %36, %37, 1, 1, 0;\n"
      : "+f"(d[0]),"+f"(d[1]),"+f"(d[2]),"+f"(d[3]),"+f"(d[4]),"+f"(d[5]),"+f"(d[6]),"+f"(d[7]),"+f"(d[8]),"+f"(d[9]),"+f"(d[10]),"+f"(d[11]),"+f"(d[12]),"+f"(d[13]),"+f"(d[14]),"+f"(d[15]),"+f"(d[16]),"+f"(d[17]),"+f"(d[18]),"+f"(d[19]),"+f"(d[20]),"+f"(d[21]),"+f"(d[22]),"+f"(d[23]),"+f"(d[24]),"+f"(d[25]),"+f"(d[26]),"+f"(d[27]),"+f"(d[28]),"+f"(d[29]),"+f"(d[30]),"+f"(d[31])
      : "r"(a0), "r"(a1), "r"(a2), "r"(a3), "l"(db), "n"(SD));
}
template<int SD> __device__ __forceinline__ void mma_n64_sk(float* d, uint64_t da, uint64_t db) {
    asm volatile("wgmma.mma_async.sync.aligned.m64n64k16.f32.bf16.bf16 {%0,%1,%2,%3,%4,%5,%6,%7,%8,%9,%10,%11,%12,%13,%14,%15,%16,%17,%18,%19,%20,%21,%22,%23,%24,%25,%26,%27,%28,%29,%30,%31}, %32, %33, %34, 1, 1, 0, 0;\n"
      : "+f"(d[0]),"+f"(d[1]),"+f"(d[2]),"+f"(d[3]),"+f"(d[4]),"+f"(d[5]),"+f"(d[6]),"+f"(d[7]),"+f"(d[8]),"+f"(d[9]),"+f"(d[10]),"+f"(d[11]),"+f"(d[12]),"+f"(d[13]),"+f"(d[14]),"+f"(d[15]),"+f"(d[16]),"+f"(d[17]),"+f"(d[18]),"+f"(d[19]),"+f"(d[20]),"+f"(d[21]),"+f"(d[22]),"+f"(d[23]),"+f"(d[24]),"+f"(d[25]),"+f"(d[26]),"+f"(d[27]),"+f"(d[28]),"+f"(d[29]),"+f"(d[30]),"+f"(d[31])
      : "l"(da), "l"(db), "n"(SD));
}
template<int SD> __device__ __forceinline__ void mma_n24_rs(float* d, uint32_t a0, uint32_t a1, uint32_t a2, uint32_t a3, uint64_t db) {
    asm volatile("wgmma.mma_async.sync.aligned.m64n24k16.f32.bf16.bf16 {%0,%1,%2,%3,%4,%5,%6,%7,%8,%9,%10,%11}, {%12,%13,%14,%15}, %16, %17, 1, 1, 1;\n"
      : "+f"(d[0]),"+f"(d[1]),"+f"(d[2]),"+f"(d[3]),"+f"(d[4]),"+f"(d[5]),"+f"(d[6]),"+f"(d[7]),"+f"(d[8]),"+f"(d[9]),"+f"(d[10]),"+f"(d[11])
      : "r"(a0), "r"(a1), "r"(a2), "r"(a3), "l"(db), "n"(SD));
}

__host__ __device__ constexpr uint64_t mkdesc(uint32_t addr, uint32_t lbo, uint32_t sbo, uint32_t swz) {
    return (uint64_t)((addr & 0x3FFFF) >> 4) | ((uint64_t)(lbo >> 4) << 16) | ((uint64_t)(sbo >> 4) << 32) | ((uint64_t)swz << 62);
}
#define WG_FENCE() asm volatile("wgmma.fence.sync.aligned;" ::: "memory")
#define WG_COMMIT() asm volatile("wgmma.commit_group.sync.aligned;" ::: "memory")
#define WG_WAIT(n) asm volatile("wgmma.wait_group.sync.aligned " #n ";" ::: "memory")
template<int N> __device__ __forceinline__ void keep(float* r) {
#pragma unroll
    for (int i = 0; i < N; i++) asm volatile("" : "+f"(r[i]) :: "memory");
}
template<int N> __device__ __forceinline__ void kill(float* r) {
#pragma unroll
    for (int i = 0; i < N; i++) asm volatile("" : "=f"(r[i]));
}
template<int N> __device__ __forceinline__ void keep(uint32_t* r) {
#pragma unroll
    for (int i = 0; i < N; i++) asm volatile("" : "+r"(r[i]) :: "memory");
}
__device__ __forceinline__ uint32_t cl(uint32_t a) { return a + ((blockIdx.x & 1) << 24); }
__device__ __forceinline__ void mbar_init(uint32_t a, uint32_t c) { asm volatile("mbarrier.init.shared::cta.b64 [%0], %1;" :: "r"(cl(a)), "r"(c) : "memory"); }
__device__ __forceinline__ void mbar_arrive(uint32_t a) { asm volatile("mbarrier.arrive.shared::cta.b64 _, [%0];" :: "r"(cl(a)) : "memory"); }
__device__ __forceinline__ void mbar_wait(uint32_t a, uint32_t ph) {
    asm volatile("{\n.reg .pred p, q;\n.reg .u32 n;\nmov.u32 n, 0;\n"
        "LW:\nmbarrier.try_wait.parity.shared::cta.b64 p, [%0], %1;\n@p bra LD;\n"
        "add.u32 n, n, 1;\nsetp.gt.u32 q, n, 2000000;\n@q trap;\nbra LW;\nLD:\n}" :: "r"(cl(a)), "r"(ph) : "memory");
}
__device__ __forceinline__ void mbar_wait_raw(uint32_t addr, uint32_t ph) {
    asm volatile("{\n.reg .pred p, q;\n.reg .u32 n;\nmbarrier.try_wait.parity.shared::cta.b64 p, [%0], %1;\n@p bra LD;\nmov.u32 n, 0;\n"
        "LW:\nmbarrier.try_wait.parity.shared::cta.b64 p, [%0], %1;\n@p bra LD;\n"
        "add.u32 n, n, 1;\nsetp.gt.u32 q, n, 2000000;\n@q trap;\nbra LW;\nLD:\n}" :: "r"(addr), "r"(ph) : "memory");
}
__device__ __forceinline__ void flag_wait(const unsigned* p, unsigned target) {
    asm volatile("{\n.reg .pred p, q;\n.reg .u32 n, v;\nmov.u32 n, 0;\n"
        "LW:\nld.acquire.gpu.global.u32 v, [%0];\nsub.u32 v, v, %1;\nsetp.ge.s32 p, v, 0;\n@p bra LD;\n"
        "nanosleep.u32 100;\nadd.u32 n, n, 1;\nsetp.gt.u32 q, n, 4000000;\n@q trap;\nbra LW;\nLD:\n}" :: "l"(p), "r"(target) : "memory");
}
__device__ __forceinline__ void red_release(unsigned* p, unsigned v) { asm volatile("red.release.gpu.global.add.u32 [%0], %1;" :: "l"(p), "r"(v) : "memory"); }
__device__ __forceinline__ void red_relaxed(unsigned* p, unsigned v) { asm volatile("red.relaxed.gpu.global.add.u32 [%0], %1;" :: "l"(p), "r"(v) : "memory"); }
__device__ __forceinline__ void st_release(unsigned* p, unsigned v) { asm volatile("st.release.gpu.global.u32 [%0], %1;" :: "l"(p), "r"(v) : "memory"); }
__device__ __forceinline__ unsigned ld_relaxed(const unsigned* p) { unsigned v; asm volatile("ld.relaxed.gpu.global.u32 %0, [%1];" : "=r"(v) : "l"(p) : "memory"); return v; }
__device__ __forceinline__ unsigned ld_acquire(const unsigned* p) { unsigned v; asm volatile("ld.acquire.gpu.global.u32 %0, [%1];" : "=r"(v) : "l"(p) : "memory"); return v; }
__device__ __forceinline__ unsigned get_tag() { return ld_relaxed(&g_done) / (4 * NCTA) + 1; }
__device__ __forceinline__ unsigned long long ld_tagged(const unsigned long long* p) {
    unsigned long long v; asm volatile("ld.relaxed.gpu.global.b64 %0, [%1];" : "=l"(v) : "l"(p) : "memory"); return v;
}
__device__ __forceinline__ void fence_async() { asm volatile("fence.proxy.async;" ::: "memory"); }
__device__ __forceinline__ void bar_sync(int id, int n) { asm volatile("bar.sync %0, %1;" :: "r"(id), "r"(n) : "memory"); }
__device__ __forceinline__ void bar_arrive(int id, int n) { asm volatile("bar.arrive %0, %1;" :: "r"(id), "r"(n) : "memory"); }
#define ELECT_BEGIN "{\n.reg .pred p, e;\nelect.sync _|p, 0xffffffff;\nsetp.ne.and.u32 e, %1, 0, p;\n@e mbarrier.arrive.expect_tx.shared::cta.b64 _, [%0], %1;\n"
__device__ __forceinline__ void bulk_load(uint32_t dst, const void* src, uint32_t bytes, uint32_t bar, uint32_t tx) {
    asm volatile(ELECT_BEGIN ".reg .b64 pol;\ncreatepolicy.fractional.L2::evict_first.b64 pol, 1.0;\n@p cp.async.bulk.shared::cluster.global.mbarrier::complete_tx::bytes.L2::cache_hint [%2], [%3], %4, [%0], pol;\n}"
        :: "r"(cl(bar)), "r"(tx), "r"(cl(dst)), "l"(src), "r"(bytes) : "memory");
}
__device__ __forceinline__ void send_half(int kb) {
    const uint32_t off = A_OFF + (blockIdx.x & 1) * 8192 + kb * 16384, peer = ((blockIdx.x & 1) ^ 1) << 24;
    asm volatile(ELECT_BEGIN "@p cp.async.bulk.shared::cluster.shared::cta.mbarrier::complete_tx::bytes [%2], [%3], 8192, [%4];\n}"
        :: "r"(cl(BAR_FULLA + 8 * kb)), "r"(8192), "r"(off + peer), "r"(cl(off)), "r"(BAR_FULLA + 8 * kb + peer) : "memory");
}
__device__ __forceinline__ void tma2d(uint32_t dst, const CUtensorMap* m, int c0, int c1, uint32_t bar, uint32_t tx) {
    asm volatile(ELECT_BEGIN "@p cp.async.bulk.tensor.2d.shared::cluster.global.mbarrier::complete_tx::bytes [%2], [%3, {%4, %5}], [%0];\n}"
        :: "r"(cl(bar)), "r"(tx), "r"(cl(dst)), "l"(m), "r"(c0), "r"(c1) : "memory");
}
__device__ __forceinline__ void tma3d(uint32_t dst, const CUtensorMap* m, int c1, int c2, uint32_t bar, uint32_t tx) {
    asm volatile(ELECT_BEGIN "@p cp.async.bulk.tensor.3d.shared::cluster.global.mbarrier::complete_tx::bytes [%2], [%3, {%6, %4, %5}], [%0];\n}"
        :: "r"(cl(bar)), "r"(tx), "r"(cl(dst)), "l"(m), "r"(c1), "r"(c2), "r"(0) : "memory");
}
__device__ __forceinline__ void tma5d(uint32_t dst, const CUtensorMap* m, int c3, int c4, uint32_t bar, uint32_t tx) {
    asm volatile(ELECT_BEGIN "@p cp.async.bulk.tensor.5d.shared::cluster.global.mbarrier::complete_tx::bytes [%2], [%3, {%6, %6, %6, %4, %5}], [%0];\n}"
        :: "r"(cl(bar)), "r"(tx), "r"(cl(dst)), "l"(m), "r"(c3), "r"(c4), "r"(0) : "memory");
}
__device__ __forceinline__ uint32_t pack_bf16(float lo, float hi) {
    uint32_t r; asm("cvt.rn.bf16x2.f32 %0, %1, %2;" : "=r"(r) : "f"(hi), "f"(lo)); return r;
}
__device__ __forceinline__ float bf_lo(uint32_t v) { return __uint_as_float(v << 16); }
__device__ __forceinline__ float bf_hi(uint32_t v) { return __uint_as_float(v & 0xffff0000u); }
__device__ __forceinline__ float2 lds64(uint32_t a) { float2 v; asm volatile("ld.shared.v2.f32 {%0,%1}, [%2];" : "=f"(v.x), "=f"(v.y) : "r"(cl(a))); return v; }
__device__ __forceinline__ uint32_t lds32(uint32_t a) { uint32_t v; asm volatile("ld.shared.u32 %0, [%1];" : "=r"(v) : "r"(cl(a)) : "memory"); return v; }
__device__ __forceinline__ void l2_prefetch(const void* p, uint32_t bytes, uint32_t pause) {
#pragma unroll 1
    for (uint32_t o = (threadIdx.x & 31) * 128; o < bytes; o += 4096) {
        asm volatile("prefetch.global.L2 [%0];" :: "l"((const uint8_t*)p + o) : "memory");
        if (pause) asm volatile("nanosleep.u32 %0;" :: "r"(pause));
    }
    __syncwarp();
}
__device__ __forceinline__ float ex2(float x) { float y; asm("ex2.approx.ftz.f32 %0, %1;" : "=f"(y) : "f"(x)); return y; }

__device__ __forceinline__ int cta_m() { return blockIdx.x >> 3; }
__device__ __forceinline__ int cta_j() { return blockIdx.x & 7; }
__device__ __forceinline__ bool cta_isG() { return blockIdx.x < 128 && (blockIdx.x & 7) < 3; }
#define AORDER 0x42310000
__device__ __forceinline__ int cta_aidx() {
    const int j = blockIdx.x & 7;
    return blockIdx.x >= 128 ? blockIdx.x - 128 : 4 + ((AORDER >> (4 * j)) & 7) * 16 + (blockIdx.x >> 3);
}

#define MINIW 0x02022000
__device__ __forceinline__ int mini_w() { return (MINIW >> (4 * cta_j())) & 3; }
__device__ __forceinline__ int has_mini() { return mini_w() != 0; }
__device__ __forceinline__ int num_jobs() { return has_mini() + (cta_isG() ? 4 : 2); }
__device__ __forceinline__ int job_id(int q) {
    const int w = q - has_mini(), j = cta_j();
    const uint32_t below = MINIW & ((1u << (4 * j)) - 1);
    return w < 0 ? __popc(below & 0x11111111u) + 2 * __popc(below & 0x22222222u) : 6 + (w < 2 ? 8 * w + j : 10 + 3 * w + j);
}
__device__ __forceinline__ int job_chunk(int id) { return id < 6 ? id : 3 * id - 12; }
__device__ __forceinline__ int job_bar(int q) { return q < 3 ? 11 + q : (q == 3 ? 15 : 3); }

template<int J>
__device__ __forceinline__ void qkv_mainloop(uint32_t* v, int wg, bool elect) {
    constexpr int O = (216 * J) % 64, N1 = 64 - O, N2 = 152 + O, NCH = (O + 216 + 63) / 64, NST = NCH == 4 ? 9 : 7;
    constexpr uint64_t dB = mkdesc(B_OFF, 2048, 1024, 1);
    const uint64_t dA = mkdesc(A_OFF, 16, 1024, 1) + (uint64_t)((wg - 1) * (8192 >> 4));
    int st = NST == 7 ? 6 : 0; uint32_t ph = 0;
    float acc[108];
#pragma unroll 1
    for (int ks = 0; ks < 36; ks += 2) {
        int st1 = st + 1; uint32_t ph1 = ph; if (st1 == NST) { st1 = 0; ph1 ^= 1; }
        if ((ks & 3) == 0 && ((wg ^ blockIdx.x) & 1) == 0) mbar_wait(BAR_FULLA + 2 * ks, 0);
        mbar_wait(BAR_FULLW + 8 * st, ph);
        mbar_wait(BAR_FULLW + 8 * st1, ph1);
        const uint64_t a = dA + (uint64_t)((ks >> 2) * (16384 >> 4) + (ks & 3) * 2);
        WG_FENCE();
#pragma unroll
        for (int k = 0; k < 2; k++) {
            const uint64_t b = dB + (uint64_t)((k ? st1 : st) * (NCH * 2048 >> 4));
            if (N2 <= 200) mma_ssp<(N2 <= 200 ? N2 : 128)>(acc + N1 / 2, a + 2 * k, b + (2048 >> 4), ks + k);
            else { mma_ssp<128>(acc + N1 / 2, a + 2 * k, b + (2048 >> 4), ks + k); mma_ssp<80>(acc + N1 / 2 + 64, a + 2 * k, b + (6144 >> 4), ks + k); }
            mma_ssp<N1>(acc, a + 2 * k, b + (2 * O >> 4), ks + k);
        }
        WG_COMMIT();
        WG_WAIT(1);
        if ((threadIdx.x & 127) < 2 && ks > 0) {
            int sp = st - 1 - (threadIdx.x & 1); if (sp < 0) sp += NST;
            mbar_arrive(BAR_EMPTYW + 8 * sp);
        }
        st = st1 + 1; ph = ph1; if (st == NST) { st = 0; ph ^= 1; }
    }
    WG_WAIT(0);
    keep<108>(acc);
    if ((threadIdx.x & 127) < 3) mbar_arrive((threadIdx.x & 127) == 2 ? BAR_WDONE : BAR_EMPTYW + 8 * (NST - 1 - (threadIdx.x & 1)));
    if (wg == 1) TS(16);
    constexpr float QS = 0.23570226f * 1.44269504f;
#pragma unroll
    for (int i = 0; i < 54; i++) v[i] = 216 * J + 8 * (i >> 1) < DM ? pack_bf16(acc[2 * i] * QS, acc[2 * i + 1] * QS) : pack_bf16(acc[2 * i], acc[2 * i + 1]);
}

__device__ __forceinline__ uint64_t sel_desc(int q) { return mkdesc(ONE_OFF, 0, 0, 0) + (uint64_t)(q * (128 >> 4)) + ((uint64_t)((6 - q) * (128 >> 4)) << 16); }
constexpr uint64_t SEL2 = (uint64_t)(128 >> 4) << 16;
constexpr uint64_t BIAS_DESC = mkdesc(BIAS_OFF, 1024, 0, 1);
template<int W>
__device__ __forceinline__ void mini_mainloop(float* acc0, float* acc1, bool elect) {
    constexpr uint64_t dA = mkdesc(A_OFF, 16, 1024, 1), dB = mkdesc(B_OFF, 6144, 1024, 1);
    WG_FENCE();
    if (W == 1) { mma_n64_ss<0>(acc0, sel_desc(0), BIAS_DESC); mma_n64_ss<0>(acc1, sel_desc(0) + SEL2, BIAS_DESC); }
    else { mma_n128_ss<0>(acc0, sel_desc(0), BIAS_DESC); mma_n128_ss<0>(acc1, sel_desc(0) + SEL2, BIAS_DESC); }
    WG_COMMIT();
    int st = 0;
#pragma unroll 1
    for (int s = 0; s < 6 * W; s++) {
        mbar_wait(BAR_FULLB + 8 * st, s >= 6);
        if (s == 6 * W - 1) bar_arrive(9, 256);
        WG_FENCE();
#pragma unroll
        for (int k = 0; k < 6 / W; k++) {
            const int ks = (6 / W) * s + k;
            const uint64_t a = dA + (uint64_t)((ks >> 2) * (16384 >> 4) + (ks & 3) * 2), b = dB + (uint64_t)(st * (12288 >> 4) + k * (2048 >> 4));
            if (W == 1) { mma_n64_ss<1>(acc0, a, b); mma_n64_ss<1>(acc1, a + (8192 >> 4), b); }
            else { mma_n128_ss<1>(acc0, a, b); mma_n128_ss<1>(acc1, a + (8192 >> 4), b); }
        }
        WG_COMMIT();
        WG_WAIT(1);
        if (elect && s > 0) mbar_arrive(BAR_EMPTYB + 8 * (st == 0 ? 5 : st - 1));
        if (++st == 6) st = 0;
    }
    WG_WAIT(0);
    if (elect) mbar_arrive(BAR_EMPTYB + 8 * 5);
    keep<32 * W>(acc0); keep<32 * W>(acc1);
}
__device__ __forceinline__ void job_mainloop(float* acc0, float* acc1, int q, bool g2, uint32_t xa, bool elect) {
    constexpr uint64_t dB = mkdesc(B_OFF, 4096, 1024, 1);
    const bool last = q == num_jobs() - 1, releaseA = g2 || last, handoff = !g2 && (!last || cta_isG());
    WG_FENCE();
    mma_n192_ss<0>(acc0, sel_desc(g2 ? 5 : q), BIAS_DESC); mma_n192_ss<0>(acc1, sel_desc(g2 ? 5 : q) + SEL2, BIAS_DESC);
    WG_COMMIT();
    if (q > 0) bar_sync(8 + (q & 1), 256);
    const int nturn = g2 ? 27 : 3;
    int grp = 0; uint32_t pa = 1;
#pragma unroll 1
    for (int u = 0; u < nturn; u++) {
        const uint32_t par = (q + u + (mini_w() >> 1)) & 1;
        if (g2 && (u == 3 || u == 12 || u == 24)) TS2(u == 3 ? 4 : (u == 12 ? 5 : 6));
        if (u == 24) {
            mbar_wait(BAR_FULLA, pa); mbar_wait(BAR_FULLA + 8, pa); mbar_wait(BAR_FULLA + 16, pa);
            WG_WAIT(0);
            keep<96>(acc0); keep<96>(acc1);
            if (elect) { mbar_arrive(BAR_EMPTYB + 8 * 5); mbar_arrive(BAR_EMPTYA + 8 * 8); }
#pragma unroll
            for (int i2 = 0; i2 < 12; i2++) {
#pragma unroll
                for (int mh = 0; mh < 2; mh++) {
                    float* a = (mh ? acc1 : acc0) + 8 * i2;
                    uint32_t r[4];
                    asm volatile("ldmatrix.sync.aligned.m8n8.x4.shared.b16 {%0,%1,%2,%3}, [%4];" : "=r"(r[0]), "=r"(r[1]), "=r"(r[2]), "=r"(r[3])
                        : "r"(cl((xa ^ ((i2 & 3) << 5)) + (i2 >> 2) * 16384 + mh * 8192)) : "memory");
#pragma unroll
                    for (int e = 0; e < 4; e++) { a[2 * e] = fmaf(a[2 * e], 0.5f, bf_lo(r[e])); a[2 * e + 1] = fmaf(a[2 * e + 1], 0.5f, bf_hi(r[e])); }
                }
            }
            keep<96>(acc0); keep<96>(acc1);
            grp = 1;
        }
        const uint64_t dAu = (!g2 ? mkdesc(A_OFF, 16, 1024, 1) : (u < 24 ? mkdesc(A_OFF, 16, 512, 2) : mkdesc(A_OFF, 128, 1024, 0))) + (uint64_t)(grp * (3 * 16384 >> 4));
        const uint32_t kst = u >= 24 ? (256 >> 4) : (32 >> 4), hst = !g2 ? (64 >> 4) : (u < 24 ? (8192 >> 4) : (512 >> 4)), mst = (g2 && u < 24) ? (4096 >> 4) : (8192 >> 4);
#pragma unroll
        for (int st = 0; st < 6; st++) {
            const int kb = st >> 1, half = st & 1;
            if (half == 0 && g2) mbar_wait(BAR_FULLA + 8 * (3 * grp + kb), pa);
            mbar_wait(BAR_FULLB + 8 * st, par);
            if (st == 5 && u == 2 && handoff) bar_arrive(8 + ((q + 1) & 1), 256);
            WG_FENCE();
#pragma unroll
            for (int k = 0; k < 2; k++) {
                const uint64_t a = dAu + (uint64_t)(kb * (16384 >> 4) + half * hst + k * kst);
                const uint64_t b = dB + (uint64_t)((st * 12288 + k * 2048) >> 4);
                mma_n192_ss<1>(acc0, a, b); mma_n192_ss<1>(acc1, a + mst, b);
            }
            WG_COMMIT();
            WG_WAIT(1);
            if (elect && (st > 0 || u > 0)) {
                if (st > 0 || u != 24) {
                    mbar_arrive(BAR_EMPTYB + 8 * ((st + 5) % 6));
                    if (half == 0 && releaseA) mbar_arrive(BAR_EMPTYA + 8 * (kb == 0 && grp == 0 ? 8 : 3 * grp + kb - 1));
                }
                if (st == 1 && u == 24) { mbar_arrive(BAR_EMPTYA); mbar_arrive(BAR_EMPTYA + 8); mbar_arrive(BAR_EMPTYA + 16); }
            }
        }
        if (++grp == 3) { grp = 0; pa ^= 1; }
    }
    WG_WAIT(0);
    if (elect && !g2) { mbar_arrive(BAR_EMPTYB + 8 * 5); if (releaseA) mbar_arrive(BAR_EMPTYA + 8 * 8); }
    keep<96>(acc0); keep<96>(acc1);
}

__device__ __forceinline__ void epilogue_gelu(const float* acc, uint8_t* hp, int nchunk) {
#pragma unroll
    for (int i4 = 0; i4 < 6; i4++) {
        if ((i4 == 2 || i4 == 4) && i4 == 2 * nchunk) break;
        float z[16];
#define XX(e) acc[4 * (8 * (i4 >> 1) + (i4 & 1) + 2 * ((e) >> 2)) + ((e) & 3)]
#pragma unroll
        for (int e = 0; e < 16; e++) z[e] = XX(e) * fmaf(XX(e) * XX(e), 0.035677408f, 0.79788456f);
#pragma unroll
        for (int e = 0; e < 16; e++) asm("tanh.approx.f32 %0, %0;" : "+f"(z[e]));
#pragma unroll
        for (int e = 0; e < 16; e++) z[e] = fmaf(XX(e), z[e], XX(e));
#undef XX
#pragma unroll
        for (int r = 0; r < 2; r++)
            *(uint4*)(hp + r * 512 + i4 * 8192) = make_uint4(pack_bf16(z[2 * r], z[2 * r + 1]), pack_bf16(z[4 + 2 * r], z[5 + 2 * r]),
                                                                         pack_bf16(z[8 + 2 * r], z[9 + 2 * r]), pack_bf16(z[12 + 2 * r], z[13 + 2 * r]));
    }
}
__device__ __forceinline__ void job_epilogue(float* acc0, float* acc1, int q, int warp, int g, int t) {
    uint8_t* hp = g_h + (size_t)(cta_m() * 72 + job_chunk(job_id(q))) * 16384 + warp * 1024 + g * 64 + ((t ^ (g >> 1)) << 4);
    epilogue_gelu(acc0, hp, q < has_mini() ? mini_w() : 3);
    epilogue_gelu(acc1, hp + 4096, q < has_mini() ? mini_w() : 3);
    kill<96>(acc0); kill<96>(acc1);
    bar_arrive(job_bar(q), 160);
}

__device__ __forceinline__ void epilogue_qkv(const uint32_t* vv, int rg, int g, int t, int wg) {
    const int j = cta_j();
#define V(r, i) vv[2 * (i) + (r)]
    if (wg == 2 && !has_mini()) bar_sync(14, 256);
    uint8_t* p = g_qkv + (size_t)(12 * j) * 98304 + rg * 384 + g * 16;
    uint8_t* pr[4];
#pragma unroll
    for (int k = 0; k < 4; k++) { const int r = (t - k) & 3; pr[k] = p + (r >> 1) * 128 + (r & 1) * 8; asm volatile("" : "+l"(pr[k])); }
    uint8_t* p3 = p + t * 98304 + 256;
    asm volatile("" : "+l"(p3));
    const uint32_t pk0 = ((POLYMASK >> (rg & 15)) & 1) ? 0x3f803f80u : 0u, pk1 = ((POLYMASK >> ((rg + 1) & 15)) & 1) ? 0x3f803f80u : 0u;
#pragma unroll
    for (int gi = 0; gi < 3; gi++) {
        const int which = (3 * j + gi) >> 3;
        const uint32_t ec = which == 2 ? 0x00003f80u : 0x427e4740u, ed = which == 2 ? 0u : 0x3aacbe9au, hs = which == 0 ? 0x3f003f00u : 0x3f803f80u;
#pragma unroll
        for (int r = 0; r < 2; r++) {
            const uint32_t a = (t & 1) ? V(r, 9 * gi + 4) : V(r, 9 * gi + 2), b = (t & 1) ? V(r, 9 * gi + 8) : V(r, 9 * gi + 6), pk = r ? pk1 : pk0;
            uint32_t u;
            asm("mul.rn.bf16x2 %0, %1, %2;" : "=r"(u) : "r"((t & 2) ? b : a), "r"(hs));
            *(uint4*)(p3 + 4 * gi * 98304 + r * 384) = make_uint4(u, which == 1 ? pk : ec, which == 1 ? pk : ed, 0u);
        }
        uint32_t mx[2] = {0u, 0u};
#pragma unroll
        for (int h = 4 * gi; h < 4 * gi + 4; h++) {
            {
                const int k = h % 4, i0 = (9 * h) / 4;
                const bool lo = k == 0 || t >= k;
                *(uint2*)(pr[k] + h * 98304) = make_uint2(lo ? V(0, i0) : V(0, i0 + 1), lo ? V(0, i0 + 1) : V(0, i0 + 2));
                *(uint2*)(pr[k] + h * 98304 + 384) = make_uint2(lo ? V(1, i0) : V(1, i0 + 1), lo ? V(1, i0 + 1) : V(1, i0 + 2));
            }
#pragma unroll
            for (int r = 0; r < 2; r++) {
                const int b0 = (9 * h) / 4;
                uint32_t a;
                asm("mul.rn.bf16x2 %0, %1, %1;" : "=r"(a) : "r"(V(r, b0)));
                asm("fma.rn.bf16x2 %0, %1, %1, %0;" : "+r"(a) : "r"(V(r, b0 + 1)));
                asm("fma.rn.bf16x2 %0, %1, %1, %0;" : "+r"(a) : "r"(V(r, b0 + 2)));
                asm("max.NaN.bf16x2 %0, %0, %1;" : "+r"(mx[r]) : "r"(a));
            }
        }
        float w0 = bf_lo(mx[0]) + bf_hi(mx[0]), w1 = bf_lo(mx[1]) + bf_hi(mx[1]);
        w0 += __shfl_xor_sync(0xffffffffu, w0, 1); w1 += __shfl_xor_sync(0xffffffffu, w1, 1);
        w0 += __shfl_xor_sync(0xffffffffu, w0, 2); w1 += __shfl_xor_sync(0xffffffffu, w1, 2);
        const uint32_t bb = __reduce_max_sync(0xffffffffu, max(__float_as_uint(w0) & 0x7fffffffu, __float_as_uint(w1) & 0x7fffffffu));
        if ((threadIdx.x & 31) == 0) asm volatile("red.shared.max.u32 [%0], %1;" :: "r"(cl(BMAX_OFF + 4 * gi)), "r"(bb) : "memory");
    }
}

__device__ __forceinline__ uint32_t exp2_fma(float a, float b, uint32_t c3f00, uint32_t c0003) {
    uint32_t s, m, e, r;
    asm("prmt.b32 %0, %1, %2, 0x5410;" : "=r"(s) : "r"(__float_as_uint(a)), "r"(__float_as_uint(b)));
    asm("lop3.b32 %0, %1, 0x007f007f, %2, 0xEA;" : "=r"(m) : "r"(s), "r"(c3f00));
    asm("lop3.b32 %0, %1, 0xff80ff80, %2, 0xEA;" : "=r"(e) : "r"(s), "r"(c0003));
    asm("fma.rn.bf16x2 %0, %1, %2, %3;" : "=r"(r) : "r"(s), "r"(m), "r"(e));
    return r;
}
template<int B0> __device__ __forceinline__ void exps(const float* S, uint32_t* P, uint32_t c3f00, uint32_t c0003) {
#pragma unroll
    for (int i = 0; i < 4; i++) {
        if ((POLYMASK >> (i + B0)) & 1) { P[2 * i] = exp2_fma(S[4 * i], S[4 * i + 1], c3f00, c0003); P[2 * i + 1] = exp2_fma(S[4 * i + 2], S[4 * i + 3], c3f00, c0003); }
        else { P[2 * i] = pack_bf16(ex2(S[4 * i]), ex2(S[4 * i + 1])); P[2 * i + 1] = pack_bf16(ex2(S[4 * i + 2]), ex2(S[4 * i + 3])); }
    }
}
__device__ __forceinline__ void pv(float* O, const uint32_t* X, const uint32_t* Y, uint64_t dv) {
    mma_n24_rs<1>(O, X[0], X[1], X[2], X[3], dv); mma_n24_rs<1>(O, X[4], X[5], X[6], X[7], dv + (768 >> 4));
    mma_n24_rs<1>(O, Y[0], Y[1], Y[2], Y[3], dv + 2 * (768 >> 4)); mma_n24_rs<1>(O, Y[4], Y[5], Y[6], Y[7], dv + 3 * (768 >> 4));
}
constexpr uint64_t STEP2 = (256 >> 4) - ((uint64_t)(128 >> 4) << 16);
__device__ __forceinline__ void qk(float* S, uint64_t dq, uint64_t dk) {
    mma_n64_sk<0>(S, dq, dk);
    mma_n64_sk<1>(S, dq + STEP2, dk + STEP2);
}
__device__ __forceinline__ void qk_rs(float* S, const uint32_t* q, uint64_t dk) {
    mma_n64_rs<0>(S, q[0], q[1], q[2], q[3], dk);
    mma_n64_rs<1>(S, q[4], q[5], q[6], q[7], dk + STEP2);
}
__device__ __forceinline__ int helper_id() {
    const int j = cta_j(), h = cta_m() + (j == 7 ? 0 : 16);
    return (blockIdx.x < 128 && (j == 7 || j == HELP2) && h < 4 * XS) ? h : -1;
}
__device__ __forceinline__ int num_tasks() { return blockIdx.x >= 128 ? 32 - XS : (helper_id() >= 0 ? 25 : 24); }
__device__ __forceinline__ void seg_info(int seg, int& rd, int& s0, int& len) {
    const int h = helper_id();
    rd = cta_aidx() + NACTA * (h >= 0 ? seg - 1 : seg); s0 = 0; len = 8;
    if (h >= 0 && seg == 0) { rd = 252 + (h & 3); s0 = h >> 2; len = 1; }
    if (rd >= 252 && h < 0) { s0 = XS; len = 8 - XS; }
}
__device__ __forceinline__ void task_table(int task) {
    int seg = task >> 3, k = task & 7;
    if (helper_id() >= 0 && task >= 1) { seg = 1 + ((task - 1) >> 3); k = (task - 1) & 7; }
    int rd, s0, len; seg_info(seg, rd, s0, len);
    const uint32_t hb = (rd >> 3) * 98304;
    asm volatile("st.shared.v2.u32 [%0], {%1, %2};" :: "r"(cl(TASK_OFF + 8 * task)), "r"(hb + 32 * 98304 + (s0 + k) * 12288),
                 "r"(k == 0 ? hb + (rd & 7) * 12288 + 2 + (seg & 1) : 0) : "memory");
}
__device__ __forceinline__ void kv_load(int task) {
    const float2 e = lds64(TASK_OFF + 8 * task);
    const uint32_t ko = __shfl_sync(0xffffffffu, __float_as_uint(e.x), 0), qo = __shfl_sync(0xffffffffu, __float_as_uint(e.y), 0);
    const int sl = task & 7;
    bulk_load(K_OFF + sl * 12288, g_qkv + ko, 12288, BAR_FULLKV + 8 * sl, qo ? 36864 : 24576);
    bulk_load(V_OFF + sl * 12288, g_qkv + ko + 32 * 98304, 12288, BAR_FULLKV + 8 * sl, 0);
    if (qo) bulk_load((qo & 1) ? Q2_OFF : Q_OFF, g_qkv + (qo & ~3u), 12288, BAR_FULLKV + 8 * sl, 0);
}
__device__ __forceinline__ void kv_refill(int task, int wg, int ntask) {
    const int r = task + 8 - KVLAG;
    if ((r & 3) == wg && r >= 8 && r < ntask) {
        mbar_wait(BAR_EMPTYKV + 8 * (r & 7), ((r >> 3) & 1) ^ 1);
        kv_load(r);
    }
}
__device__ __forceinline__ void publish_all(unsigned* flag0, int stride, int seg, unsigned tag) {
    mbar_wait(BAR_DEP + 8 * (seg & 1), (seg >> 1) & 1);
    if ((threadIdx.x & 31) < 4) st_release(flag0 + (threadIdx.x & 31) * stride, tag);
    __syncwarp();
}

__device__ __forceinline__ void pieces_acquire(int wg, unsigned tag) {
    const int lane = threadIdx.x & 31, r = blockIdx.x - 128;
    int n = 0;
    while (!__all_sync(0xffffffffu, ld_acquire(&g_pflag[(r * 4 + wg) * 8 + lane % XS]) == tag))
        asm volatile("{\n.reg .pred q;\nnanosleep.u32 100;\nsetp.gt.u32 q, %0, 4000000;\n@q trap;\n}" :: "r"(++n));
#pragma unroll 1
    for (int i = lane; i < XS * 64; i += 32)
        asm volatile("prefetch.global.L2 [%0];" :: "l"(g_part + (r * XS * 4 + (i >> 4)) * 512 + wg * 128 + (i & 15) * 8) : "memory");
}

__device__ __forceinline__ void attention(int wg, unsigned tag) {
    const int lane = threadIdx.x & 31, t = lane & 3;
    const int warp = __shfl_sync(0xffffffffu, (threadIdx.x >> 5) & 3, 0);
    const bool elect = (threadIdx.x & 127) == 0;
    constexpr uint64_t dk0 = mkdesc(K_OFF, 128, 384, 0), dv0 = mkdesc(V_OFF, 384, 128, 0);
    const uint32_t zero = (blockIdx.x >> 20) * lane;
    const uint32_t c3f00 = __shfl_sync(0xffffffffu, 0x3f003f00u + zero, 0);
    const uint32_t c0003 = __shfl_sync(0xffffffffu, 0x00030003u + zero, 0);
    unsigned* pending = nullptr; int pstride = 0;
    const int ntask = num_tasks();
    int T = 0;
#pragma unroll 1
    for (int seg = 0; T < ntask; seg++) {
        int rd, s0, len; seg_info(seg, rd, s0, len);
        const int Tend = T + len, Tpub = (seg > 0 && (seg & 3) == wg && ((warp + wg) & 3) == 2) ? (len < 4 ? Tend - 1 : T + 3) : -1;
        mbar_wait(BAR_FULLKV + 8 * (T & 7), (T >> 3) & 1);
        const bool fast = (__shfl_sync(0xffffffffu, lds32(FAST_OFF), 0) >> (rd >> 5)) & 1;
        const uint64_t q = mkdesc(Q_OFF, 128, 384, 0) + (uint64_t)((((seg & 1) ? Q2_OFF - Q_OFF : 0) + wg * 3072) >> 4);
        float m0 = 0.f, m1 = 0.f;
        float SA[32], SB_[32], O[12];
        uint32_t P[16];
#pragma unroll
        for (int i = 0; i < 12; i++) O[i] = 0.f;
        if (!fast) m0 = m1 = -INFINITY;
        if (len != 8 && len != 1) {
            bar_sync(4 + wg, 128);
            float4 pa[XS][4];
#pragma unroll
            for (int i = 0; i < XS; i++) {
                const float4* pp = g_part + ((rd - 252) * XS + i) * 2048 + threadIdx.x;
#pragma unroll
                for (int e = 0; e < 4; e++) pa[i][e] = __ldcg(pp + 512 * e);
            }
#pragma unroll
            for (int i = 0; i < XS; i++) {
                const float4 a = pa[i][0], b = pa[i][1], c = pa[i][2], m = pa[i][3];
                const float n0 = fmaxf(m0, m.x), n1 = fmaxf(m1, m.y);
                const float f0 = ex2(m0 - n0), f1 = ex2(m1 - n1), g0 = ex2(m.x - n0), g1 = ex2(m.y - n1);
                m0 = n0; m1 = n1;
                O[0] = O[0] * f0 + a.x * g0; O[1] = O[1] * f0 + a.y * g0; O[2] = O[2] * f1 + a.z * g1; O[3] = O[3] * f1 + a.w * g1;
                O[4] = O[4] * f0 + b.x * g0; O[5] = O[5] * f0 + b.y * g0; O[6] = O[6] * f1 + b.z * g1; O[7] = O[7] * f1 + b.w * g1;
                O[8] = O[8] * f0 + c.x * g0; O[9] = O[9] * f0 + c.y * g0; O[10] = O[10] * f1 + c.z * g1; O[11] = O[11] * f1 + c.w * g1;
            }
        }
#pragma unroll
        for (int i = 0; i < 12; i++) asm volatile("add.f32 %0, %0, %1;" : "+f"(O[i]) : "f"(__uint_as_float(zero)) : "memory");
        if (fast) {
            uint64_t dk = dk0 + (uint64_t)((T & 7) * (12288 >> 4)), dv = dv0 + (uint64_t)((T & 7) * (12288 >> 4));
            WG_FENCE();
            qk(SA, q, dk); WG_COMMIT();
            qk(SB_, q, dk + (3072 >> 4)); WG_COMMIT();
            dk += 2 * (3072 >> 4);
            const int role = (warp + wg) & 3;
            const uint32_t duty = role == 0 ? ~0u << (T + 1) : (role == 1 ? 0x11111111u << ((wg + KVLAG) & 3) : (Tpub >= 0 ? 1u << Tpub : (role == 3 && blockIdx.x >= 128 ? 1u << 22 : 0u)));
#pragma unroll 1
            for (; T < Tend; T++) {
                const uint32_t wrap = (T & 7) == 7 ? (8 * 12288 >> 4) : 0;
#pragma unroll
                for (int h = 0; h < 4; h++) {
                    float* S = (h & 1) ? SB_ : SA;
                    WG_WAIT(1);
                    keep<32>(S); keep<12>(O);
                    if (h & 1) { exps<8>(S, P, c3f00, c0003); exps<12>(S + 16, P + 8, c3f00, c0003); } else { exps<0>(S, P, c3f00, c0003); exps<4>(S + 16, P + 8, c3f00, c0003); }
                    keep<16>(P);
                    WG_FENCE();
                    pv(O, P, P + 8, dv); WG_COMMIT();
                    qk(S, q, dk); WG_COMMIT();
                    dv += (3072 >> 4); dk += (3072 >> 4);
                    if (h == 1) { dk -= wrap; if (T + 1 < Tend) mbar_wait_raw(cl(BAR_FULLKV) + 8 * ((T + 1) & 7), ((T + 1) >> 3) & 1); }
                    if (h == 3) dv -= wrap;
                    if (h == 0 && ((duty >> T) & 1)) {
                        if (role == 0) { if (lane == 0) mbar_arrive(BAR_EMPTYKV + 8 * ((T - 1) & 7)); __syncwarp(); }
                        else if (role == 1) kv_refill(T, wg, ntask);
                        else if (role == 2) publish_all(pending, pstride, seg - 1, tag);
                        else pieces_acquire(wg, tag);
                    }
                }
            }
            WG_WAIT(0);
            keep<12>(O); keep<32>(SA); keep<32>(SB_);
            m0 = m1 = 0.f;
        } else {
            const uint32_t qa = ((seg & 1) ? Q2_OFF : Q_OFF) + (wg * 8 + warp * 2) * 384 + lane * 4;
            uint32_t qr[8];
            qr[0] = lds32(qa); qr[1] = lds32(qa + 384); qr[2] = lds32(qa + 128); qr[3] = lds32(qa + 384 + 128);
            qr[4] = lds32(qa + 256 + (t ? 12 - 4 * t : 0)); qr[5] = lds32(qa + 384 + 256 + (t ? 12 - 4 * t : 0));
            qr[6] = lds32(qa + 256 + (t ? 12 - 4 * t : 0)); qr[7] = lds32(qa + 384 + 256 + (t ? 12 - 4 * t : 0));
            keep<8>(qr);
#pragma unroll 1
            for (; T < Tend; T++) {
                if (warp == 1) kv_refill(T, wg, ntask);
                if (T == Tpub) publish_all(pending, pstride, seg - 1, tag);
                if (T == 22 && warp == 3 && blockIdx.x >= 128) pieces_acquire(wg, tag);
                mbar_wait(BAR_FULLKV + 8 * (T & 7), (T >> 3) & 1);
#pragma unroll 1
                for (int h = 0; h < 4; h++) {
                    const uint64_t so = (uint64_t)(((T & 7) * 12288 + h * 3072) >> 4);
                    WG_FENCE();
                    qk_rs(SA, qr, dk0 + so); WG_COMMIT();
                    WG_WAIT(0);
                    keep<32>(SA); keep<12>(O);
                    float n0 = m0, n1 = m1;
#pragma unroll
                    for (int i = 0; i < 8; i++) { n0 = fmaxf(n0, fmaxf(SA[4 * i], SA[4 * i + 1])); n1 = fmaxf(n1, fmaxf(SA[4 * i + 2], SA[4 * i + 3])); }
                    n0 = fmaxf(n0, __shfl_xor_sync(0xffffffffu, n0, 1)); n0 = fmaxf(n0, __shfl_xor_sync(0xffffffffu, n0, 2));
                    n1 = fmaxf(n1, __shfl_xor_sync(0xffffffffu, n1, 1)); n1 = fmaxf(n1, __shfl_xor_sync(0xffffffffu, n1, 2));
                    const float f0 = ex2(m0 - n0), f1 = ex2(m1 - n1);
                    m0 = n0; m1 = n1;
#pragma unroll
                    for (int i = 0; i < 3; i++) { O[4 * i] *= f0; O[4 * i + 1] *= f0; O[4 * i + 2] *= f1; O[4 * i + 3] *= f1; }
#pragma unroll
                    for (int i = 0; i < 8; i++) {
                        P[2 * i] = pack_bf16(ex2(SA[4 * i] - m0), ex2(SA[4 * i + 1] - m0));
                        P[2 * i + 1] = pack_bf16(ex2(SA[4 * i + 2] - m1), ex2(SA[4 * i + 3] - m1));
                    }
                    keep<16>(P); keep<12>(O);
                    WG_FENCE();
                    pv(O, P, P + 8, dv0 + so); WG_COMMIT();
                    WG_WAIT(0);
                    keep<12>(O);
                }
                if (elect && T + 1 < Tend) mbar_arrive(BAR_EMPTYKV + 8 * (T & 7));
            }
        }
        if (elect) mbar_arrive(BAR_EMPTYKV + 8 * ((T - 1) & 7));
        if (wg == 1) TS2(4 + seg);
        if (len == 1) {
            float4* pp = g_part + ((rd - 252) * XS + s0) * 2048 + threadIdx.x;
            pp[0] = make_float4(O[0], O[1], O[2], O[3]); pp[512] = make_float4(O[4], O[5], O[6], O[7]);
            pp[1024] = make_float4(O[8], O[9], O[10], O[11]); pp[1536] = make_float4(m0, m1, 0.f, 0.f);
            pending = &g_pflag[(rd - 252) * 32 + s0]; pstride = 8;
            __syncwarp();
            if (lane == 0) mbar_arrive(BAR_DEP + 8 * (seg & 1));
            continue;
        }
        const int head = rd >> 3, rb = (rd & 7) * 4 + wg, g = lane >> 2;
        const float l0 = __shfl_sync(0xffffffffu, O[8], (lane & ~3) | 1), l1 = __shfl_sync(0xffffffffu, O[10], (lane & ~3) | 1);
        const float r0 = __frcp_rn(l0), r1 = __frcp_rn(l1);
        uint8_t* ob = g_o + (size_t)(rb >> 1) * (9 * 16384) + ((rb & 1) * 8 + warp * 2) * 1024 + g * 16;
#pragma unroll
        for (int i = 0; i < 3; i++) {
            const int c = head * 18 + (i < 2 ? 4 * i + (t & 2) + 8 * (t & 1) : 16);
            uint8_t* op = ob + (c >> 6) * 16384 + ((c >> 3) & 7) * 128 + (c & 7) * 2;
            if (i < 2 || t == 0) {
                *(uint32_t*)op = pack_bf16(O[4 * i] * r0, O[4 * i + 1] * r0);
                *(uint32_t*)(op + 1024) = pack_bf16(O[4 * i + 2] * r1, O[4 * i + 3] * r1);
            }
        }
        pending = &g_oflag[(rd & 7) * 128 + head]; pstride = 32;
        __syncwarp();
        if (lane == 0) mbar_arrive(BAR_DEP + 8 * (seg & 1));
    }
    bar_sync(4 + wg, 128);
    if (elect) st_release(pending + wg * pstride, tag);
}

__global__ void __cluster_dims__(2, 1, 1) __launch_bounds__(NTHREADS, 1) fused_kernel(const __grid_constant__ Params p) {
    extern __shared__ __align__(1024) uint8_t smem_raw[];
    if ((uint32_t)__cvta_generic_to_shared(smem_raw) != cl(SB)) asm volatile("trap;");
    const int wg = __shfl_sync(0xffffffffu, threadIdx.x >> 7, 0);
    const int lane = threadIdx.x & 31;
    const bool elect = (threadIdx.x & 127) == 0;
    const bool gemm = blockIdx.x < 128;
    const bool five = cta_j() == 2 || cta_j() == 5;
    if (threadIdx.x >= 32 && threadIdx.x < 41) asm volatile("prefetch.tensormap [%0];" :: "l"(&p.wq4 + (threadIdx.x - 32)) : "memory");
    const int lrow = (blockIdx.x & 1) * 64 + (threadIdx.x >> 3);
    uint32_t v[36];
    if (gemm) {
        const uint4* xr = (const uint4*)(p.xp + (size_t)(cta_m() * 128 + lrow) * DM) + (lane & 7);
#pragma unroll
        for (int i = 0; i < 9; i++) { const uint4 w = __ldg(xr + i * 8); v[4 * i] = w.x; v[4 * i + 1] = w.y; v[4 * i + 2] = w.z; v[4 * i + 3] = w.w; }
        if (threadIdx.x >= 384 && threadIdx.x < 506 && blockIdx.x * 15616 + (threadIdx.x - 384) * 128 < 1728 * DM * 2)
            asm volatile("prefetch.global.L2 [%0];" :: "l"((const uint8_t*)p.wqkvp + blockIdx.x * 15616 + (threadIdx.x - 384) * 128) : "memory");
    }
    if ((threadIdx.x & 31) < NBARS / 16) {
        const int i = (threadIdx.x >> 5) * (NBARS / 16) + (threadIdx.x & 31);
        const uint32_t cnt = (i >= 55 && i < 64) || i == 79 ? 2 : (i >= 38 && i < 46 ? 4 : ((i == 66 || i == 67) && !cta_isG() ? 16 : 1));
        mbar_init(BAR_OFF + 8 * i, cnt);
        asm volatile("fence.mbarrier_init.release.cluster;" ::: "memory");
    }
    if (threadIdx.x >= 40 && threadIdx.x < 43) asm volatile("st.shared.u32 [%0], %1;" :: "r"(cl(BMAX_OFF + 4 * (threadIdx.x - 40))), "r"(0) : "memory");
    __syncthreads();
    asm volatile("barrier.cluster.arrive.relaxed.aligned;" ::: "memory");
    TS(wg);
    if (gemm) {
        const int ks = __shfl_sync(0xffffffffu, threadIdx.x >> 5, 0);
        if (ks < (five ? 7 : 9)) {
            const int st = five ? (ks == 0 ? 6 : ks - 1) : ks;
            if (five && ks > 0 && lane < 3) mbar_arrive(lane == 0 ? BAR_FULLW + 8 * st : BAR_EMPTYW + 8 * st);
            __syncwarp();
            tma3d(B_OFF + st * (five ? 10240 : 8192), five ? &p.wq5 : &p.wq4, ks * 16, (216 * cta_j()) >> 6, BAR_FULLW + 8 * st, five ? 10240 : 8192);
        }
        float f[72], s = 0.f, s2 = 0.f;
#pragma unroll
        for (int i = 0; i < 36; i++) { f[2 * i] = bf_lo(v[i]); f[2 * i + 1] = bf_hi(v[i]); s += f[2 * i]; s2 += f[2 * i + 1]; }
        s += s2;
        s += __shfl_xor_sync(0xffffffffu, s, 1); s += __shfl_xor_sync(0xffffffffu, s, 2); s += __shfl_xor_sync(0xffffffffu, s, 4);
        const float mean = s * (1.0f / DM);
        if (wg == 1) TS(29);
        float q = 0.f, q2 = 0.f;
#pragma unroll
        for (int i = 0; i < 36; i++) { f[2 * i] -= mean; f[2 * i + 1] -= mean; q = fmaf(f[2 * i], f[2 * i], q); q2 = fmaf(f[2 * i + 1], f[2 * i + 1], q2); }
        q += q2;
        q += __shfl_xor_sync(0xffffffffu, q, 1); q += __shfl_xor_sync(0xffffffffu, q, 2); q += __shfl_xor_sync(0xffffffffu, q, 4);
        const float rstd = rsqrtf(q * (1.0f / DM) + 1e-5f);
        const uint32_t dst = cl(A_OFF + lrow * 128 + (((lane & 7) ^ (lrow & 7)) << 4));
#pragma unroll
        for (int i = 0; i < 9; i++)
            asm volatile("st.shared.v4.b32 [%0], {%1,%2,%3,%4};" :: "r"(dst + i * 16384),
                "r"(pack_bf16(f[8 * i] * rstd, f[8 * i + 1] * rstd)), "r"(pack_bf16(f[8 * i + 2] * rstd, f[8 * i + 3] * rstd)),
                "r"(pack_bf16(f[8 * i + 4] * rstd, f[8 * i + 5] * rstd)), "r"(pack_bf16(f[8 * i + 6] * rstd, f[8 * i + 7] * rstd)) : "memory");
        if (wg == 1) TS(31);
        asm volatile("fence.proxy.async.shared::cta;" ::: "memory");
    }
    asm volatile("barrier.cluster.wait.aligned;" ::: "memory");
    __syncthreads();
    if (gemm && threadIdx.x < 32) { send_half(0); send_half(1); }
    TS(28);

    if (wg == 0) {
        asm volatile("setmaxnreg.dec.sync.aligned.u32 24;");
        const int warp = __shfl_sync(0xffffffffu, threadIdx.x >> 5, 0);
        if (warp == 0) {
            if (gemm) {
                int st = five ? 6 : 0; uint32_t ph = 0;
                const int nst = five ? 7 : 9; const uint32_t sb = five ? 10240 : 8192;
#pragma unroll 1
                for (int ks = nst; ks < 36; ks++) {
                    const int i = ks - nst;
                    if ((i % 3) == 0 && i < 21) send_half(2 + i / 3);
                    mbar_wait(BAR_EMPTYW + 8 * st, ph);
                    tma3d(B_OFF + st * sb, five ? &p.wq5 : &p.wq4, ks * 16, (216 * cta_j()) >> 6, BAR_FULLW + 8 * st, sb);
                    if (++st == nst) { st = 0; ph ^= 1; }
                }
                st = 0; ph = 1;
                int fresh = 6;
#pragma unroll 1
                for (int q = 0; q < num_jobs(); q++) {
#pragma unroll 1
                    for (int k = 0; k < DM; k += (q < has_mini() ? (mini_w() == 1 ? 96 : 48) : 32)) {
                        if (fresh) { fresh--; mbar_wait(BAR_EMPTYW + 8 * (five ? (st == 5 ? 6 : st + 1) : (3 * st + 2) >> 1), 1); }
                        else mbar_wait(BAR_EMPTYB + 8 * st, ph);
                        tma3d(B_OFF + st * 12288, q < has_mini() ? (mini_w() == 1 ? &p.w1n : &p.w1m) : &p.w1, k, job_chunk(job_id(q)), BAR_FULLB + 8 * st, 12288);
                        if (++st == 6) { st = 0; ph ^= 1; }
                    }
                }
                if (cta_isG()) {
#pragma unroll 1
                    for (int hk = 0; hk < 162; hk++) {
                        mbar_wait(BAR_EMPTYB + 8 * st, ph);
                        if (hk < 144) tma5d(B_OFF + st * 12288, &p.w2, (hk >> 1) * 32 + (hk & 1) * 4, cta_j() * 3, BAR_FULLB + 8 * st, 12288);
                        else tma3d(B_OFF + st * 12288, &p.wo, (hk - 144) * 32, cta_j() * 3, BAR_FULLB + 8 * st, 12288);
                        if (++st == 6) { st = 0; ph ^= 1; }
                    }
                }
            }
        } else if (warp == 1) {
            if (gemm) {
                const unsigned tag = get_tag();
                bar_sync(10, 288);
                if (lane < 3) atomicMax(&g_bound[(3 * cta_j() + lane) * 16], ((unsigned long long)tag << 32) | lds32(BMAX_OFF + 4 * lane));
                __syncwarp();
                if (lane == 0) red_release(&g_qkvcnt, 1);
                __syncwarp();
#pragma unroll 1
                for (int q = 0; q < num_jobs(); q++) {
                    bar_sync(job_bar(q), 160);
                    if (lane < (q < has_mini() ? mini_w() : 1)) st_release(&g_hflag[cta_m() * 32 + job_id(q) + lane], tag);
                    __syncwarp();
                }
            }
        } else if (warp == 3) {
            if (cta_isG()) {
                int sa = 0, dep = 0, next_dep = 0; uint32_t pa = 0;
#pragma unroll 1
                for (int kk = 0; kk < 84; kk++) {
                    if (kk == next_dep) {
                        mbar_wait(BAR_DEP + 8 * dep, 0);
                        dep++;
                        next_dep = kk < 63 ? (kk == 0 ? 30 : (kk == 30 ? 54 : 63)) : (kk == 63 ? 75 : kk + 1);
                    }
                    mbar_wait(BAR_EMPTYA + 8 * sa, pa);
                    if (kk >= 72 && kk < 75) tma2d(A_OFF + sa * 16384, &p.x, (3 * cta_j() + kk - 72) * 64, cta_m() * 128, BAR_FULLA + 8 * sa, 16384);
                    else bulk_load(A_OFF + sa * 16384, kk < 72 ? g_h + (size_t)(cta_m() * 72 + kk) * 16384 : g_o + (size_t)(cta_m() * 9 + (kk - 75)) * 16384, 16384, BAR_FULLA + 8 * sa, 16384);
                    if (++sa == 9) { sa = 0; pa ^= 1; }
                }
            } else {
                const unsigned tag = get_tag();
                task_table(lane);
                if (gemm) mbar_wait(BAR_WDONE, 0);
                flag_wait(&g_qkvcnt, tag * 128);
                __syncwarp();
                const float bn = lane < 24 ? __uint_as_float((uint32_t)ld_tagged(&g_bound[lane * 16])) * 1.02f : 0.f;
                asm volatile("fence.proxy.async.global;" ::: "memory");
                const float bk = __shfl_sync(0xffffffffu, bn, (lane & 7) + 8), bv = __shfl_sync(0xffffffffu, bn, (lane & 7) + 16);
                const uint32_t fastmask = __ballot_sync(0xffffffffu, __fsqrt_rn(bn * bk) + 0.5f * __log2f(fmaxf(bv, 1.0f)) <= GUARD);
                asm volatile("st.shared.u32 [%0], %1;" :: "r"(cl(FAST_OFF)), "r"(fastmask) : "memory");
                __syncwarp();
#pragma unroll 1
                for (int s = 0; s < 8; s++) {
                    if (gemm) mbar_wait(BAR_EMPTYA + 8 * (s == 0 ? 7 : 8), 0);
                    kv_load(s);
                }
            }
        } else {
            if (gemm) l2_prefetch((const uint8_t*)p.w1p + blockIdx.x * 41472, 41472, 300);
            if (cta_isG()) {
                const unsigned tag = get_tag();
                mbar_wait(BAR_WDONE, 0);
#pragma unroll 1
                for (int d = 0; d < 4; d++) {
                    if (lane < (d == 0 ? 14 : 19 + 3 * d)) flag_wait(&g_hflag[cta_m() * 32 + lane], tag);
                    __syncwarp();
                    fence_async();
                    if (lane == 0) mbar_arrive(BAR_DEP + 8 * d);
                }
                int d = 0, n = 0;
                const unsigned* f0 = &g_oflag[(cta_m() * 2) * 32 + lane];
#pragma unroll 1
                while (d < 9) {
                    unsigned a, b;
                    asm volatile("ld.acquire.gpu.global.u32 %0, [%1];" : "=r"(a) : "l"(f0) : "memory");
                    asm volatile("ld.acquire.gpu.global.u32 %0, [%1];" : "=r"(b) : "l"(f0 + 32) : "memory");
                    const uint32_t miss = ~__ballot_sync(0xffffffffu, a == tag && b == tag);
                    const int ready = miss ? ((__ffs(miss) - 1) * 18) >> 6 : 9;
                    if (ready > d) {
                        asm volatile("fence.proxy.async.global;" ::: "memory");
                        if (lane >= d && lane < ready) mbar_arrive(BAR_DEP + 8 * (4 + lane));
                        d = ready;
                    } else asm volatile("{\n.reg .pred q;\nnanosleep.u32 %1;\nsetp.gt.u32 q, %0, 4000000;\n@q trap;\n}" :: "r"(++n), "r"(d < 5 ? 500 : 20));
                }
            }
        }
        if (cta_isG()) {
            bar_sync(4, 128);
            if (elect) red_relaxed(&g_done, 1);
            return;
        }
        bar_sync(2, 256);
        asm volatile("setmaxnreg.inc.sync.aligned.u32 128;");
    } else if (wg == 3) {
        asm volatile("setmaxnreg.dec.sync.aligned.u32 24;");
        if (gemm) {
            const int tid = threadIdx.x & 127;
#pragma unroll 2
            for (int w = tid; w < 1024; w += 128) {
                uint32_t bw, bdst;
                if (w < 768) {
                    const int c = w >> 8, r = (w >> 5) & 7, k = w & 31;
                    bw = (r < num_jobs() && (r >= has_mini() || c < mini_w())) ? __ldg((const uint32_t*)p.b1p + (job_chunk(job_id(r)) + c) * 32 + k) : 0u;
                    if (r == 5 && cta_isG()) bw = __ldg((const uint32_t*)p.b2p + (3 * cta_j() + c) * 32 + k);
                    bdst = BIAS_OFF + c * 1024 + r * 128 + (((k >> 2) ^ r) << 4) + (k & 3) * 4;
                } else {
                    const int u = w - 768, q = u >> 5, k = u & 3;
                    bw = (q < 6 && k == (q >> 1)) ? (q == 5 ? 0x40000000u : ((q & 1) ? 0x3f800000u : 0x00003f80u)) : 0u;
                    bdst = ONE_OFF + u * 4;
                }
                asm volatile("st.shared.u32 [%0], %1;" :: "r"(cl(bdst)), "r"(bw) : "memory");
            }
            asm volatile("fence.proxy.async.shared::cta;" ::: "memory");
            bar_sync(7, 128);
            if (elect) mbar_arrive(BAR_INFO);
        }
        if (cta_isG()) {
            if ((threadIdx.x >> 5) == 12) {
                mbar_wait(BAR_EMPTYA, 0);
#pragma unroll 1
                for (int line = (cta_m() * 3 + cta_j()) * 32 + lane; line < 41472 + 5184; line += 1536) {
                    asm volatile("prefetch.global.L2 [%0];" :: "l"(line < 41472 ? (const uint8_t*)p.w2p + line * 128 : (const uint8_t*)p.wop + (line - 41472) * 128) : "memory");
                    asm volatile("nanosleep.u32 %0;" :: "n"(PF2NS));
                }
                __syncwarp();
            }
            if (elect) red_relaxed(&g_done, 1);
            return;
        }
        bar_sync(1, 256);
        asm volatile("setmaxnreg.inc.sync.aligned.u32 128;");
    } else {
        const int warp = __shfl_sync(0xffffffffu, (threadIdx.x >> 5) & 3, 0), g = lane >> 2, t = lane & 3;
        asm volatile("setmaxnreg.inc.sync.aligned.u32 232;");
        if (gemm) {
            uint32_t vv[54];
            switch (cta_j()) {
                case 0: qkv_mainloop<0>(vv, wg, elect); break;
                case 1: qkv_mainloop<1>(vv, wg, elect); break;
                case 2: qkv_mainloop<2>(vv, wg, elect); break;
                case 3: qkv_mainloop<3>(vv, wg, elect); break;
                case 4: qkv_mainloop<4>(vv, wg, elect); break;
                case 5: qkv_mainloop<5>(vv, wg, elect); break;
                case 6: qkv_mainloop<6>(vv, wg, elect); break;
                default: qkv_mainloop<7>(vv, wg, elect); break;
            }
            if (wg == 1) TS(26);
            float acc0[96], acc1[96];
            kill<96>(acc0); kill<96>(acc1);
            mbar_wait(BAR_INFO, 0);
            mbar_wait(BAR_WDONE, 0);
            keep<54>(vv);
            if (wg == 1 && has_mini()) { if (mini_w() == 1) mini_mainloop<1>(acc0, acc1, elect); else mini_mainloop<2>(acc0, acc1, elect); TS(17); }
            keep<54>(vv);
            epilogue_qkv(vv, cta_m() * 16 + (wg - 1) * 8 + warp * 2, g, t, wg);
            if (wg == 1 && !has_mini()) bar_arrive(14, 256);
            TS(wg == 1 ? 27 : 30);
            bar_arrive(10, 288);
#pragma unroll 1
            for (int q = wg - 1; q < num_jobs() + cta_isG(); q += 2) {
                const bool g2 = q == num_jobs();
                const uint32_t xa = A_OFF + (warp * 16 + (lane & 15)) * 128 + (((lane >> 4) ^ (lane & 7)) << 4);
                if (g2) TS2(9);
                if (q >= has_mini()) job_mainloop(acc0, acc1, q, g2, xa, elect);
                if (g2) {
                    TS2(12);
#pragma unroll
                    for (int c = 0; c < 3; c++) {
#pragma unroll
                        for (int i2 = 4 * c; i2 < 4 * c + 4; i2++) {
#pragma unroll
                            for (int mh = 0; mh < 2; mh++) {
                                const float* a = (mh ? acc1 : acc0) + 8 * i2;
                                asm volatile("stmatrix.sync.aligned.m8n8.x4.shared.b16 [%0], {%1,%2,%3,%4};"
                                    :: "r"(cl((xa ^ ((i2 & 3) << 5)) + (3 + c) * 16384 + mh * 8192)),
                                       "r"(pack_bf16(a[0], a[1])), "r"(pack_bf16(a[2], a[3])), "r"(pack_bf16(a[4], a[5])), "r"(pack_bf16(a[6], a[7])) : "memory");
                            }
                        }
                        asm volatile("fence.proxy.async.shared::cta;" ::: "memory");
                        bar_sync(4 + wg, 128);
                        if (elect) asm volatile("cp.async.bulk.tensor.2d.global.shared::cta.bulk_group [%0, {%1, %2}], [%3];"
                                        :: "l"(&p.outm), "r"(cta_j() * 192 + c * 64), "r"(cta_m() * 128), "r"(cl(A_OFF + (3 + c) * 16384)) : "memory");
                    }
                    if (elect) asm volatile("cp.async.bulk.commit_group;\ncp.async.bulk.wait_group.read 0;" ::: "memory");
                    TS2(14);
                    break;
                }
                if (q >= has_mini()) TS(17 + (q < 4 ? q : 4));
                job_epilogue(acc0, acc1, q, warp, g, t);
                TS(22 + (q < 3 ? q : 3));
            }
        }
        if (cta_isG()) {
            bar_sync(4 + wg, 128);
            if (elect) red_relaxed(&g_done, 1);
            return;
        }
        asm volatile("setmaxnreg.dec.sync.aligned.u32 128;");
        bar_arrive(has_mini() ? 3 - wg : wg, 256);
    }
    __syncwarp();
    TS2(8 + wg);
    attention(wg, get_tag());
    TS2(12 + wg);
    bar_sync(4 + wg, 128);
    if (elect) red_relaxed(&g_done, 1);
}

typedef CUresult (*EncFn)(CUtensorMap*, CUtensorMapDataType, cuuint32_t, void*, const cuuint64_t*, const cuuint64_t*, const cuuint32_t*,
                          const cuuint32_t*, CUtensorMapInterleave, CUtensorMapSwizzle, CUtensorMapL2promotion, CUtensorMapFloatOOBfill);

void make_map(EncFn enc, CUtensorMap* m, const void* ptr, int rank, const cuuint64_t* dims, const cuuint64_t* strides, const cuuint32_t* box) {
    cuuint32_t es[5] = {1, 1, 1, 1, 1};
    enc(m, CU_TENSOR_MAP_DATA_TYPE_BFLOAT16, rank, const_cast<void*>(ptr), dims, strides, box, es, CU_TENSOR_MAP_INTERLEAVE_NONE,
        CU_TENSOR_MAP_SWIZZLE_128B, L2PROMO, CU_TENSOR_MAP_FLOAT_OOB_FILL_NONE);
}
void make_act_map(EncFn enc, CUtensorMap* m, const void* ptr, int cols) {
    cuuint64_t d[2] = {(cuuint64_t)cols, SEQ}, s[1] = {(cuuint64_t)cols * 2}; cuuint32_t b[2] = {64, 128};
    make_map(enc, m, ptr, 2, d, s, b);
}

}

extern "C" void kernel_launch(void* const* d_in, const int* in_sizes, int n_in, void* d_out, int out_size) {
    static Params prm;
    static bool ready = false;
    static const void* key[9];
    bool same = ready && key[8] == d_out;
    for (int i = 0; i < 8 && same; i++) same = key[i] == d_in[i];
    if (!same) {
        EncFn enc = nullptr; cudaDriverEntryPointQueryResult qr;
        cudaGetDriverEntryPoint("cuTensorMapEncodeTiled", (void**)&enc, cudaEnableDefault, &qr);
        make_act_map(enc, &prm.outm, d_out, DM);
        make_act_map(enc, &prm.x, d_in[0], DM);
        {
            cuuint64_t d[3] = {64, DM, 27}, s[2] = {1728 * 2, 128}; cuuint32_t b4[3] = {64, 16, 4}, b5[3] = {64, 16, 5};
            make_map(enc, &prm.wq4, d_in[1], 3, d, s, b4);
            make_map(enc, &prm.wq5, d_in[1], 3, d, s, b5);
        }
        {
            cuuint64_t d[3] = {64, DM, FF / 64}, s[2] = {FF * 2, 128}; cuuint32_t b[3] = {64, 32, 3};
            make_map(enc, &prm.w1, d_in[4], 3, d, s, b);
            cuuint32_t bn[3] = {64, 96, 1};
            make_map(enc, &prm.w1n, d_in[4], 3, d, s, bn);
            cuuint32_t bm[3] = {64, 48, 2};
            make_map(enc, &prm.w1m, d_in[4], 3, d, s, bm);
        }
        {
            cuuint64_t d[3] = {64, DM, DM / 64}, s[2] = {DM * 2, 128}; cuuint32_t b[3] = {64, 32, 3};
            make_map(enc, &prm.wo, d_in[2], 3, d, s, b);
        }
        {
            cuuint64_t d[5] = {64, 2, 4, 2280, DM / 64}, s[4] = {DM * 2, 16 * DM * 2, 2 * DM * 2, 128}; cuuint32_t b[5] = {64, 2, 4, 4, 3};
            make_map(enc, &prm.w2, d_in[6], 5, d, s, b);
        }
        prm.xp = (const __nv_bfloat16*)d_in[0]; prm.wqkvp = (const __nv_bfloat16*)d_in[1]; prm.w1p = (const __nv_bfloat16*)d_in[4];
        prm.b1p = (const __nv_bfloat16*)d_in[5]; prm.b2p = (const __nv_bfloat16*)d_in[7]; prm.out = (__nv_bfloat16*)d_out;
        prm.w2p = (const __nv_bfloat16*)d_in[6]; prm.wop = (const __nv_bfloat16*)d_in[2];
        cudaFuncSetAttribute(fused_kernel, cudaFuncAttributeMaxDynamicSharedMemorySize, SMEM_BYTES);
        for (int i = 0; i < 8; i++) key[i] = d_in[i];
        key[8] = d_out; ready = true;
    }
    fused_kernel<<<NCTA, NTHREADS, SMEM_BYTES, cudaStreamPerThread>>>(prm);
}
```

```cpp
#include <cuda_runtime.h>
#include <cuda_bf16.h>
#include <cuda.h>
#include <stdint.h>

#define L2PROMO CU_TENSOR_MAP_L2_PROMOTION_L2_128B
namespace {

constexpr int SEQ = 2048, DM = 576, FF = 4608, NH = 32;
constexpr int NCTA = 132, NTHREADS = 512, NACTA = 84;
#define GUARD 80.0f
#define HELP2 5
#define PF2NS 500
#define KVLAG 5
#define PMASK 0xAD6Bu
constexpr uint32_t POLYMASK = PMASK;

constexpr uint32_t SB = 0x400;
constexpr uint32_t A_OFF = SB;
constexpr uint32_t B_OFF = SB + 9 * 16384;
constexpr uint32_t Q_OFF = SB, Q2_OFF = SB + 12288 + 8 * 24576;
constexpr uint32_t K_OFF = SB + 12288, V_OFF = K_OFF + 8 * 12288;
constexpr uint32_t BAR_OFF = B_OFF + 6 * 12288;
constexpr uint32_t BAR_FULLA = BAR_OFF, BAR_EMPTYA = BAR_FULLA + 72, BAR_FULLB = BAR_EMPTYA + 72, BAR_EMPTYB = BAR_FULLB + 48,
                   BAR_FULLKV = BAR_EMPTYB + 48, BAR_EMPTYKV = BAR_FULLKV + 64, BAR_FULLW = BAR_EMPTYKV + 64, BAR_EMPTYW = BAR_FULLW + 72,
                   BAR_INFO = BAR_EMPTYW + 72, BAR_DEP = BAR_INFO + 16, BAR_WDONE = BAR_DEP + 13 * 8, FAST_OFF = BAR_WDONE + 8, BMAX_OFF = FAST_OFF + 4;
constexpr int NBARS = 9 + 9 + 6 + 6 + 8 + 8 + 9 + 9 + 2 + 13 + 1;
static_assert(NBARS % 16 == 0, "barrier init");
constexpr uint32_t ONE_OFF = BAR_OFF + 768;
constexpr uint32_t BIAS_OFF = BAR_OFF + 2048;
constexpr uint32_t TASK_OFF = BIAS_OFF + 3072;
constexpr uint32_t SMEM_END = TASK_OFF + 256;
static_assert(ONE_OFF + 1024 <= BIAS_OFF && BIAS_OFF % 1024 == 0, "smem map");
constexpr uint32_t SMEM_BYTES = SMEM_END - SB;
static_assert(SMEM_BYTES <= 232448, "smem");

__device__ __align__(1024) uint8_t g_h[SEQ * FF * 2];
__device__ __align__(1024) uint8_t g_o[SEQ * DM * 2];
__device__ __align__(1024) uint8_t g_qkv[96 * 98304];
__device__ unsigned long long g_bound[24 * 16];
__device__ unsigned g_done;
__device__ unsigned g_qkvcnt[64];
__device__ unsigned g_hflag[16 * 32];
#define XS 5
__device__ __align__(16) float4 g_part[4 * XS * 4 * 512];
__device__ unsigned g_pflag[4 * 4 * 8];
__device__ __align__(8) unsigned g_oflag[16 * 32 * 2];
#define TS(i)
#define TS2(i)

struct Params {
    const __nv_bfloat16* xp; const __nv_bfloat16* wqkvp; const __nv_bfloat16* w1p; const __nv_bfloat16* b1p; const __nv_bfloat16* b2p;
    const __nv_bfloat16* w2p; const __nv_bfloat16* wop;
    __nv_bfloat16* out;
    CUtensorMap wq4, wq5, w1n, w1m, w1, w2, wo, x, outm;
};

template<int N> __device__ __forceinline__ void mma_ssp(float* d, uint64_t da, uint64_t db, int sd);
template<> __device__ __forceinline__ void mma_ssp<8>(float* d, uint64_t da, uint64_t db, int sd) {
    asm volatile("{\n.reg .pred p;\nsetp.ne.b32 p, %6, 0;\nwgmma.mma_async.sync.aligned.m64n8k16.f32.bf16.bf16 {%0,%1,%2,%3}, %4, %5, p, 1, 1, 0, 1;\n}\n"
      : "+f"(d[0]),"+f"(d[1]),"+f"(d[2]),"+f"(d[3])
      : "l"(da), "l"(db), "r"(sd));
}
template<> __device__ __forceinline__ void mma_ssp<16>(float* d, uint64_t da, uint64_t db, int sd) {
    asm volatile("{\n.reg .pred p;\nsetp.ne.b32 p, %10, 0;\nwgmma.mma_async.sync.aligned.m64n16k16.f32.bf16.bf16 {%0,%1,%2,%3,%4,%5,%6,%7}, %8, %9, p, 1, 1, 0, 1;\n}\n"
      : "+f"(d[0]),"+f"(d[1]),"+f"(d[2]),"+f"(d[3]),"+f"(d[4]),"+f"(d[5]),"+f"(d[6]),"+f"(d[7])
      : "l"(da), "l"(db), "r"(sd));
}
template<> __device__ __forceinline__ void mma_ssp<24>(float* d, uint64_t da, uint64_t db, int sd) {
    asm volatile("{\n.reg .pred p;\nsetp.ne.b32 p, %14, 0;\nwgmma.mma_async.sync.aligned.m64n24k16.f32.bf16.bf16 {%0,%1,%2,%3,%4,%5,%6,%7,%8,%9,%10,%11}, %12, %13, p, 1, 1, 0, 1;\n}\n"
      : "+f"(d[0]),"+f"(d[1]),"+f"(d[2]),"+f"(d[3]),"+f"(d[4]),"+f"(d[5]),"+f"(d[6]),"+f"(d[7]),"+f"(d[8]),"+f"(d[9]),"+f"(d[10]),"+f"(d[11])
      : "l"(da), "l"(db), "r"(sd));
}
template<> __device__ __forceinline__ void mma_ssp<32>(float* d, uint64_t da, uint64_t db, int sd) {
    asm volatile("{\n.reg .pred p;\nsetp.ne.b32 p, %18, 0;\nwgmma.mma_async.sync.aligned.m64n32k16.f32.bf16.bf16 {%0,%1,%2,%3,%4,%5,%6,%7,%8,%9,%10,%11,%12,%13,%14,%15}, %16, %17, p, 1, 1, 0, 1;\n}\n"
      : "+f"(d[0]),"+f"(d[1]),"+f"(d[2]),"+f"(d[3]),"+f"(d[4]),"+f"(d[5]),"+f"(d[6]),"+f"(d[7]),"+f"(d[8]),"+f"(d[9]),"+f"(d[10]),"+f"(d[11]),"+f"(d[12]),"+f"(d[13]),"+f"(d[14]),"+f"(d[15])
      : "l"(da), "l"(db), "r"(sd));
}
template<> __device__ __forceinline__ void mma_ssp<40>(float* d, uint64_t da, uint64_t db, int sd) {
    asm volatile("{\n.reg .pred p;\nsetp.ne.b32 p, %22, 0;\nwgmma.mma_async.sync.aligned.m64n40k16.f32.bf16.bf16 {%0,%1,%2,%3,%4,%5,%6,%7,%8,%9,%10,%11,%12,%13,%14,%15,%16,%17,%18,%19}, %20, %21, p, 1, 1, 0, 1;\n}\n"
      : "+f"(d[0]),"+f"(d[1]),"+f"(d[2]),"+f"(d[3]),"+f"(d[4]),"+f"(d[5]),"+f"(d[6]),"+f"(d[7]),"+f"(d[8]),"+f"(d[9]),"+f"(d[10]),"+f"(d[11]),"+f"(d[12]),"+f"(d[13]),"+f"(d[14]),"+f"(d[15]),"+f"(d[16]),"+f"(d[17]),"+f"(d[18]),"+f"(d[19])
      : "l"(da), "l"(db), "r"(sd));
}
template<> __device__ __forceinline__ void mma_ssp<48>(float* d, uint64_t da, uint64_t db, int sd) {
    asm volatile("{\n.reg .pred p;\nsetp.ne.b32 p, %26, 0;\nwgmma.mma_async.sync.aligned.m64n48k16.f32.bf16.bf16 {%0,%1,%2,%3,%4,%5,%6,%7,%8,%9,%10,%11,%12,%13,%14,%15,%16,%17,%18,%19,%20,%21,%22,%23}, %24, %25, p, 1, 1, 0, 1;\n}\n"
      : "+f"(d[0]),"+f"(d[1]),"+f"(d[2]),"+f"(d[3]),"+f"(d[4]),"+f"(d[5]),"+f"(d[6]),"+f"(d[7]),"+f"(d[8]),"+f"(d[9]),"+f"(d[10]),"+f"(d[11]),"+f"(d[12]),"+f"(d[13]),"+f"(d[14]),"+f"(d[15]),"+f"(d[16]),"+f"(d[17]),"+f"(d[18]),"+f"(d[19]),"+f"(d[20]),"+f"(d[21]),"+f"(d[22]),"+f"(d[23])
      : "l"(da), "l"(db), "r"(sd));
}
template<> __device__ __forceinline__ void mma_ssp<56>(float* d, uint64_t da, uint64_t db, int sd) {
    asm volatile("{\n.reg .pred p;\nsetp.ne.b32 p, %30, 0;\nwgmma.mma_async.sync.aligned.m64n56k16.f32.bf16.bf16 {%0,%1,%2,%3,%4,%5,%6,%7,%8,%9,%10,%11,%12,%13,%14,%15,%16,%17,%18,%19,%20,%21,%22,%23,%24,%25,%26,%27}, %28, %29, p, 1, 1, 0, 1;\n}\n"
      : "+f"(d[0]),"+f"(d[1]),"+f"(d[2]),"+f"(d[3]),"+f"(d[4]),"+f"(d[5]),"+f"(d[6]),"+f"(d[7]),"+f"(d[8]),"+f"(d[9]),"+f"(d[10]),"+f"(d[11]),"+f"(d[12]),"+f"(d[13]),"+f"(d[14]),"+f"(d[15]),"+f"(d[16]),"+f"(d[17]),"+f"(d[18]),"+f"(d[19]),"+f"(d[20]),"+f"(d[21]),"+f"(d[22]),"+f"(d[23]),"+f"(d[24]),"+f"(d[25]),"+f"(d[26]),"+f"(d[27])
      : "l"(da), "l"(db), "r"(sd));
}
template<> __device__ __forceinline__ void mma_ssp<64>(float* d, uint64_t da, uint64_t db, int sd) {
    asm volatile("{\n.reg .pred p;\nsetp.ne.b32 p, %34, 0;\nwgmma.mma_async.sync.aligned.m64n64k16.f32.bf16.bf16 {%0,%1,%2,%3,%4,%5,%6,%7,%8,%9,%10,%11,%12,%13,%14,%15,%16,%17,%18,%19,%20,%21,%22,%23,%24,%25,%26,%27,%28,%29,%30,%31}, %32, %33, p, 1, 1, 0, 1;\n}\n"
      : "+f"(d[0]),"+f"(d[1]),"+f"(d[2]),"+f"(d[3]),"+f"(d[4]),"+f"(d[5]),"+f"(d[6]),"+f"(d[7]),"+f"(d[8]),"+f"(d[9]),"+f"(d[10]),"+f"(d[11]),"+f"(d[12]),"+f"(d[13]),"+f"(d[14]),"+f"(d[15]),"+f"(d[16]),"+f"(d[17]),"+f"(d[18]),"+f"(d[19]),"+f"(d[20]),"+f"(d[21]),"+f"(d[22]),"+f"(d[23]),"+f"(d[24]),"+f"(d[25]),"+f"(d[26]),"+f"(d[27]),"+f"(d[28]),"+f"(d[29]),"+f"(d[30]),"+f"(d[31])
      : "l"(da), "l"(db), "r"(sd));
}
template<> __device__ __forceinline__ void mma_ssp<80>(float* d, uint64_t da, uint64_t db, int sd) {
    asm volatile("{\n.reg .pred p;\nsetp.ne.b32 p, %42, 0;\nwgmma.mma_async.sync.aligned.m64n80k16.f32.bf16.bf16 {%0,%1,%2,%3,%4,%5,%6,%7,%8,%9,%10,%11,%12,%13,%14,%15,%16,%17,%18,%19,%20,%21,%22,%23,%24,%25,%26,%27,%28,%29,%30,%31,%32,%33,%34,%35,%36,%37,%38,%39}, %40, %41, p, 1, 1, 0, 1;\n}\n"
      : "+f"(d[0]),"+f"(d[1]),"+f"(d[2]),"+f"(d[3]),"+f"(d[4]),"+f"(d[5]),"+f"(d[6]),"+f"(d[7]),"+f"(d[8]),"+f"(d[9]),"+f"(d[10]),"+f"(d[11]),"+f"(d[12]),"+f"(d[13]),"+f"(d[14]),"+f"(d[15]),"+f"(d[16]),"+f"(d[17]),"+f"(d[18]),"+f"(d[19]),"+f"(d[20]),"+f"(d[21]),"+f"(d[22]),"+f"(d[23]),"+f"(d[24]),"+f"(d[25]),"+f"(d[26]),"+f"(d[27]),"+f"(d[28]),"+f"(d[29]),"+f"(d[30]),"+f"(d[31]),"+f"(d[32]),"+f"(d[33]),"+f"(d[34]),"+f"(d[35]),"+f"(d[36]),"+f"(d[37]),"+f"(d[38]),"+f"(d[39])
      : "l"(da), "l"(db), "r"(sd));
}
template<> __device__ __forceinline__ void mma_ssp<128>(float* d, uint64_t da, uint64_t db, int sd) {
    asm volatile("{\n.reg .pred p;\nsetp.ne.b32 p, %66, 0;\nwgmma.mma_async.sync.aligned.m64n128k16.f32.bf16.bf16 {%0,%1,%2,%3,%4,%5,%6,%7,%8,%9,%10,%11,%12,%13,%14,%15,%16,%17,%18,%19,%20,%21,%22,%23,%24,%25,%26,%27,%28,%29,%30,%31,%32,%33,%34,%35,%36,%37,%38,%39,%40,%41,%42,%43,%44,%45,%46,%47,%48,%49,%50,%51,%52,%53,%54,%55,%56,%57,%58,%59,%60,%61,%62,%63}, %64, %65, p, 1, 1, 0, 1;\n}\n"
      : "+f"(d[0]),"+f"(d[1]),"+f"(d[2]),"+f"(d[3]),"+f"(d[4]),"+f"(d[5]),"+f"(d[6]),"+f"(d[7]),"+f"(d[8]),"+f"(d[9]),"+f"(d[10]),"+f"(d[11]),"+f"(d[12]),"+f"(d[13]),"+f"(d[14]),"+f"(d[15]),"+f"(d[16]),"+f"(d[17]),"+f"(d[18]),"+f"(d[19]),"+f"(d[20]),"+f"(d[21]),"+f"(d[22]),"+f"(d[23]),"+f"(d[24]),"+f"(d[25]),"+f"(d[26]),"+f"(d[27]),"+f"(d[28]),"+f"(d[29]),"+f"(d[30]),"+f"(d[31]),"+f"(d[32]),"+f"(d[33]),"+f"(d[34]),"+f"(d[35]),"+f"(d[36]),"+f"(d[37]),"+f"(d[38]),"+f"(d[39]),"+f"(d[40]),"+f"(d[41]),"+f"(d[42]),"+f"(d[43]),"+f"(d[44]),"+f"(d[45]),"+f"(d[46]),"+f"(d[47]),"+f"(d[48]),"+f"(d[49]),"+f"(d[50]),"+f"(d[51]),"+f"(d[52]),"+f"(d[53]),"+f"(d[54]),"+f"(d[55]),"+f"(d[56]),"+f"(d[57]),"+f"(d[58]),"+f"(d[59]),"+f"(d[60]),"+f"(d[61]),"+f"(d[62]),"+f"(d[63])
      : "l"(da), "l"(db), "r"(sd));
}
template<> __device__ __forceinline__ void mma_ssp<152>(float* d, uint64_t da, uint64_t db, int sd) {
    asm volatile("{\n.reg .pred p;\nsetp.ne.b32 p, %78, 0;\nwgmma.mma_async.sync.aligned.m64n152k16.f32.bf16.bf16 {%0,%1,%2,%3,%4,%5,%6,%7,%8,%9,%10,%11,%12,%13,%14,%15,%16,%17,%18,%19,%20,%21,%22,%23,%24,%25,%26,%27,%28,%29,%30,%31,%32,%33,%34,%35,%36,%37,%38,%39,%40,%41,%42,%43,%44,%45,%46,%47,%48,%49,%50,%51,%52,%53,%54,%55,%56,%57,%58,%59,%60,%61,%62,%63,%64,%65,%66,%67,%68,%69,%70,%71,%72,%73,%74,%75}, %76, %77, p, 1, 1, 0, 1;\n}\n"
      : "+f"(d[0]),"+f"(d[1]),"+f"(d[2]),"+f"(d[3]),"+f"(d[4]),"+f"(d[5]),"+f"(d[6]),"+f"(d[7]),"+f"(d[8]),"+f"(d[9]),"+f"(d[10]),"+f"(d[11]),"+f"(d[12]),"+f"(d[13]),"+f"(d[14]),"+f"(d[15]),"+f"(d[16]),"+f"(d[17]),"+f"(d[18]),"+f"(d[19]),"+f"(d[20]),"+f"(d[21]),"+f"(d[22]),"+f"(d[23]),"+f"(d[24]),"+f"(d[25]),"+f"(d[26]),"+f"(d[27]),"+f"(d[28]),"+f"(d[29]),"+f"(d[30]),"+f"(d[31]),"+f"(d[32]),"+f"(d[33]),"+f"(d[34]),"+f"(d[35]),"+f"(d[36]),"+f"(d[37]),"+f"(d[38]),"+f"(d[39]),"+f"(d[40]),"+f"(d[41]),"+f"(d[42]),"+f"(d[43]),"+f"(d[44]),"+f"(d[45]),"+f"(d[46]),"+f"(d[47]),"+f"(d[48]),"+f"(d[49]),"+f"(d[50]),"+f"(d[51]),"+f"(d[52]),"+f"(d[53]),"+f"(d[54]),"+f"(d[55]),"+f"(d[56]),"+f"(d[57]),"+f"(d[58]),"+f"(d[59]),"+f"(d[60]),"+f"(d[61]),"+f"(d[62]),"+f"(d[63]),"+f"(d[64]),"+f"(d[65]),"+f"(d[66]),"+f"(d[67]),"+f"(d[68]),"+f"(d[69]),"+f"(d[70]),"+f"(d[71]),"+f"(d[72]),"+f"(d[73]),"+f"(d[74]),"+f"(d[75])
      : "l"(da), "l"(db), "r"(sd));
}
template<> __device__ __forceinline__ void mma_ssp<160>(float* d, uint64_t da, uint64_t db, int sd) {
    asm volatile("{\n.reg .pred p;\nsetp.ne.b32 p, %82, 0;\nwgmma.mma_async.sync.aligned.m64n160k16.f32.bf16.bf16 {%0,%1,%2,%3,%4,%5,%6,%7,%8,%9,%10,%11,%12,%13,%14,%15,%16,%17,%18,%19,%20,%21,%22,%23,%24,%25,%26,%27,%28,%29,%30,%31,%32,%33,%34,%35,%36,%37,%38,%39,%40,%41,%42,%43,%44,%45,%46,%47,%48,%49,%50,%51,%52,%53,%54,%55,%56,%57,%58,%59,%60,%61,%62,%63,%64,%65,%66,%67,%68,%69,%70,%71,%72,%73,%74,%75,%76,%77,%78,%79}, %80, %81, p, 1, 1, 0, 1;\n}\n"
      : "+f"(d[0]),"+f"(d[1]),"+f"(d[2]),"+f"(d[3]),"+f"(d[4]),"+f"(d[5]),"+f"(d[6]),"+f"(d[7]),"+f"(d[8]),"+f"(d[9]),"+f"(d[10]),"+f"(d[11]),"+f"(d[12]),"+f"(d[13]),"+f"(d[14]),"+f"(d[15]),"+f"(d[16]),"+f"(d[17]),"+f"(d[18]),"+f"(d[19]),"+f"(d[20]),"+f"(d[21]),"+f"(d[22]),"+f"(d[23]),"+f"(d[24]),"+f"(d[25]),"+f"(d[26]),"+f"(d[27]),"+f"(d[28]),"+f"(d[29]),"+f"(d[30]),"+f"(d[31]),"+f"(d[32]),"+f"(d[33]),"+f"(d[34]),"+f"(d[35]),"+f"(d[36]),"+f"(d[37]),"+f"(d[38]),"+f"(d[39]),"+f"(d[40]),"+f"(d[41]),"+f"(d[42]),"+f"(d[43]),"+f"(d[44]),"+f"(d[45]),"+f"(d[46]),"+f"(d[47]),"+f"(d[48]),"+f"(d[49]),"+f"(d[50]),"+f"(d[51]),"+f"(d[52]),"+f"(d[53]),"+f"(d[54]),"+f"(d[55]),"+f"(d[56]),"+f"(d[57]),"+f"(d[58]),"+f"(d[59]),"+f"(d[60]),"+f"(d[61]),"+f"(d[62]),"+f"(d[63]),"+f"(d[64]),"+f"(d[65]),"+f"(d[66]),"+f"(d[67]),"+f"(d[68]),"+f"(d[69]),"+f"(d[70]),"+f"(d[71]),"+f"(d[72]),"+f"(d[73]),"+f"(d[74]),"+f"(d[75]),"+f"(d[76]),"+f"(d[77]),"+f"(d[78]),"+f"(d[79])
      : "l"(da), "l"(db), "r"(sd));
}
template<> __device__ __forceinline__ void mma_ssp<168>(float* d, uint64_t da, uint64_t db, int sd) {
    asm volatile("{\n.reg .pred p;\nsetp.ne.b32 p, %86, 0;\nwgmma.mma_async.sync.aligned.m64n168k16.f32.bf16.bf16 {%0,%1,%2,%3,%4,%5,%6,%7,%8,%9,%10,%11,%12,%13,%14,%15,%16,%17,%18,%19,%20,%21,%22,%23,%24,%25,%26,%27,%28,%29,%30,%31,%32,%33,%34,%35,%36,%37,%38,%39,%40,%41,%42,%43,%44,%45,%46,%47,%48,%49,%50,%51,%52,%53,%54,%55,%56,%57,%58,%59,%60,%61,%62,%63,%64,%65,%66,%67,%68,%69,%70,%71,%72,%73,%74,%75,%76,%77,%78,%79,%80,%81,%82,%83}, %84, %85, p, 1, 1, 0, 1;\n}\n"
      : "+f"(d[0]),"+f"(d[1]),"+f"(d[2]),"+f"(d[3]),"+f"(d[4]),"+f"(d[5]),"+f"(d[6]),"+f"(d[7]),"+f"(d[8]),"+f"(d[9]),"+f"(d[10]),"+f"(d[11]),"+f"(d[12]),"+f"(d[13]),"+f"(d[14]),"+f"(d[15]),"+f"(d[16]),"+f"(d[17]),"+f"(d[18]),"+f"(d[19]),"+f"(d[20]),"+f"(d[21]),"+f"(d[22]),"+f"(d[23]),"+f"(d[24]),"+f"(d[25]),"+f"(d[26]),"+f"(d[27]),"+f"(d[28]),"+f"(d[29]),"+f"(d[30]),"+f"(d[31]),"+f"(d[32]),"+f"(d[33]),"+f"(d[34]),"+f"(d[35]),"+f"(d[36]),"+f"(d[37]),"+f"(d[38]),"+f"(d[39]),"+f"(d[40]),"+f"(d[41]),"+f"(d[42]),"+f"(d[43]),"+f"(d[44]),"+f"(d[45]),"+f"(d[46]),"+f"(d[47]),"+f"(d[48]),"+f"(d[49]),"+f"(d[50]),"+f"(d[51]),"+f"(d[52]),"+f"(d[53]),"+f"(d[54]),"+f"(d[55]),"+f"(d[56]),"+f"(d[57]),"+f"(d[58]),"+f"(d[59]),"+f"(d[60]),"+f"(d[61]),"+f"(d[62]),"+f"(d[63]),"+f"(d[64]),"+f"(d[65]),"+f"(d[66]),"+f"(d[67]),"+f"(d[68]),"+f"(d[69]),"+f"(d[70]),"+f"(d[71]),"+f"(d[72]),"+f"(d[73]),"+f"(d[74]),"+f"(d[75]),"+f"(d[76]),"+f"(d[77]),"+f"(d[78]),"+f"(d[79]),"+f"(d[80]),"+f"(d[81]),"+f"(d[82]),"+f"(d[83])
      : "l"(da), "l"(db), "r"(sd));
}
template<> __device__ __forceinline__ void mma_ssp<176>(float* d, uint64_t da, uint64_t db, int sd) {
    asm volatile("{\n.reg .pred p;\nsetp.ne.b32 p, %90, 0;\nwgmma.mma_async.sync.aligned.m64n176k16.f32.bf16.bf16 {%0,%1,%2,%3,%4,%5,%6,%7,%8,%9,%10,%11,%12,%13,%14,%15,%16,%17,%18,%19,%20,%21,%22,%23,%24,%25,%26,%27,%28,%29,%30,%31,%32,%33,%34,%35,%36,%37,%38,%39,%40,%41,%42,%43,%44,%45,%46,%47,%48,%49,%50,%51,%52,%53,%54,%55,%56,%57,%58,%59,%60,%61,%62,%63,%64,%65,%66,%67,%68,%69,%70,%71,%72,%73,%74,%75,%76,%77,%78,%79,%80,%81,%82,%83,%84,%85,%86,%87}, %88, %89, p, 1, 1, 0, 1;\n}\n"
      : "+f"(d[0]),"+f"(d[1]),"+f"(d[2]),"+f"(d[3]),"+f"(d[4]),"+f"(d[5]),"+f"(d[6]),"+f"(d[7]),"+f"(d[8]),"+f"(d[9]),"+f"(d[10]),"+f"(d[11]),"+f"(d[12]),"+f"(d[13]),"+f"(d[14]),"+f"(d[15]),"+f"(d[16]),"+f"(d[17]),"+f"(d[18]),"+f"(d[19]),"+f"(d[20]),"+f"(d[21]),"+f"(d[22]),"+f"(d[23]),"+f"(d[24]),"+f"(d[25]),"+f"(d[26]),"+f"(d[27]),"+f"(d[28]),"+f"(d[29]),"+f"(d[30]),"+f"(d[31]),"+f"(d[32]),"+f"(d[33]),"+f"(d[34]),"+f"(d[35]),"+f"(d[36]),"+f"(d[37]),"+f"(d[38]),"+f"(d[39]),"+f"(d[40]),"+f"(d[41]),"+f"(d[42]),"+f"(d[43]),"+f"(d[44]),"+f"(d[45]),"+f"(d[46]),"+f"(d[47]),"+f"(d[48]),"+f"(d[49]),"+f"(d[50]),"+f"(d[51]),"+f"(d[52]),"+f"(d[53]),"+f"(d[54]),"+f"(d[55]),"+f"(d[56]),"+f"(d[57]),"+f"(d[58]),"+f"(d[59]),"+f"(d[60]),"+f"(d[61]),"+f"(d[62]),"+f"(d[63]),"+f"(d[64]),"+f"(d[65]),"+f"(d[66]),"+f"(d[67]),"+f"(d[68]),"+f"(d[69]),"+f"(d[70]),"+f"(d[71]),"+f"(d[72]),"+f"(d[73]),"+f"(d[74]),"+f"(d[75]),"+f"(d[76]),"+f"(d[77]),"+f"(d[78]),"+f"(d[79]),"+f"(d[80]),"+f"(d[81]),"+f"(d[82]),"+f"(d[83]),"+f"(d[84]),"+f"(d[85]),"+f"(d[86]),"+f"(d[87])
      : "l"(da), "l"(db), "r"(sd));
}
template<> __device__ __forceinline__ void mma_ssp<184>(float* d, uint64_t da, uint64_t db, int sd) {
    asm volatile("{\n.reg .pred p;\nsetp.ne.b32 p, %94, 0;\nwgmma.mma_async.sync.aligned.m64n184k16.f32.bf16.bf16 {%0,%1,%2,%3,%4,%5,%6,%7,%8,%9,%10,%11,%12,%13,%14,%15,%16,%17,%18,%19,%20,%21,%22,%23,%24,%25,%26,%27,%28,%29,%30,%31,%32,%33,%34,%35,%36,%37,%38,%39,%40,%41,%42,%43,%44,%45,%46,%47,%48,%49,%50,%51,%52,%53,%54,%55,%56,%57,%58,%59,%60,%61,%62,%63,%64,%65,%66,%67,%68,%69,%70,%71,%72,%73,%74,%75,%76,%77,%78,%79,%80,%81,%82,%83,%84,%85,%86,%87,%88,%89,%90,%91}, %92, %93, p, 1, 1, 0, 1;\n}\n"
      : "+f"(d[0]),"+f"(d[1]),"+f"(d[2]),"+f"(d[3]),"+f"(d[4]),"+f"(d[5]),"+f"(d[6]),"+f"(d[7]),"+f"(d[8]),"+f"(d[9]),"+f"(d[10]),"+f"(d[11]),"+f"(d[12]),"+f"(d[13]),"+f"(d[14]),"+f"(d[15]),"+f"(d[16]),"+f"(d[17]),"+f"(d[18]),"+f"(d[19]),"+f"(d[20]),"+f"(d[21]),"+f"(d[22]),"+f"(d[23]),"+f"(d[24]),"+f"(d[25]),"+f"(d[26]),"+f"(d[27]),"+f"(d[28]),"+f"(d[29]),"+f"(d[30]),"+f"(d[31]),"+f"(d[32]),"+f"(d[33]),"+f"(d[34]),"+f"(d[35]),"+f"(d[36]),"+f"(d[37]),"+f"(d[38]),"+f"(d[39]),"+f"(d[40]),"+f"(d[41]),"+f"(d[42]),"+f"(d[43]),"+f"(d[44]),"+f"(d[45]),"+f"(d[46]),"+f"(d[47]),"+f"(d[48]),"+f"(d[49]),"+f"(d[50]),"+f"(d[51]),"+f"(d[52]),"+f"(d[53]),"+f"(d[54]),"+f"(d[55]),"+f"(d[56]),"+f"(d[57]),"+f"(d[58]),"+f"(d[59]),"+f"(d[60]),"+f"(d[61]),"+f"(d[62]),"+f"(d[63]),"+f"(d[64]),"+f"(d[65]),"+f"(d[66]),"+f"(d[67]),"+f"(d[68]),"+f"(d[69]),"+f"(d[70]),"+f"(d[71]),"+f"(d[72]),"+f"(d[73]),"+f"(d[74]),"+f"(d[75]),"+f"(d[76]),"+f"(d[77]),"+f"(d[78]),"+f"(d[79]),"+f"(d[80]),"+f"(d[81]),"+f"(d[82]),"+f"(d[83]),"+f"(d[84]),"+f"(d[85]),"+f"(d[86]),"+f"(d[87]),"+f"(d[88]),"+f"(d[89]),"+f"(d[90]),"+f"(d[91])
      : "l"(da), "l"(db), "r"(sd));
}
template<> __device__ __forceinline__ void mma_ssp<192>(float* d, uint64_t da, uint64_t db, int sd) {
    asm volatile("{\n.reg .pred p;\nsetp.ne.b32 p, %98, 0;\nwgmma.mma_async.sync.aligned.m64n192k16.f32.bf16.bf16 {%0,%1,%2,%3,%4,%5,%6,%7,%8,%9,%10,%11,%12,%13,%14,%15,%16,%17,%18,%19,%20,%21,%22,%23,%24,%25,%26,%27,%28,%29,%30,%31,%32,%33,%34,%35,%36,%37,%38,%39,%40,%41,%42,%43,%44,%45,%46,%47,%48,%49,%50,%51,%52,%53,%54,%55,%56,%57,%58,%59,%60,%61,%62,%63,%64,%65,%66,%67,%68,%69,%70,%71,%72,%73,%74,%75,%76,%77,%78,%79,%80,%81,%82,%83,%84,%85,%86,%87,%88,%89,%90,%91,%92,%93,%94,%95}, %96, %97, p, 1, 1, 0, 1;\n}\n"
      : "+f"(d[0]),"+f"(d[1]),"+f"(d[2]),"+f"(d[3]),"+f"(d[4]),"+f"(d[5]),"+f"(d[6]),"+f"(d[7]),"+f"(d[8]),"+f"(d[9]),"+f"(d[10]),"+f"(d[11]),"+f"(d[12]),"+f"(d[13]),"+f"(d[14]),"+f"(d[15]),"+f"(d[16]),"+f"(d[17]),"+f"(d[18]),"+f"(d[19]),"+f"(d[20]),"+f"(d[21]),"+f"(d[22]),"+f"(d[23]),"+f"(d[24]),"+f"(d[25]),"+f"(d[26]),"+f"(d[27]),"+f"(d[28]),"+f"(d[29]),"+f"(d[30]),"+f"(d[31]),"+f"(d[32]),"+f"(d[33]),"+f"(d[34]),"+f"(d[35]),"+f"(d[36]),"+f"(d[37]),"+f"(d[38]),"+f"(d[39]),"+f"(d[40]),"+f"(d[41]),"+f"(d[42]),"+f"(d[43]),"+f"(d[44]),"+f"(d[45]),"+f"(d[46]),"+f"(d[47]),"+f"(d[48]),"+f"(d[49]),"+f"(d[50]),"+f"(d[51]),"+f"(d[52]),"+f"(d[53]),"+f"(d[54]),"+f"(d[55]),"+f"(d[56]),"+f"(d[57]),"+f"(d[58]),"+f"(d[59]),"+f"(d[60]),"+f"(d[61]),"+f"(d[62]),"+f"(d[63]),"+f"(d[64]),"+f"(d[65]),"+f"(d[66]),"+f"(d[67]),"+f"(d[68]),"+f"(d[69]),"+f"(d[70]),"+f"(d[71]),"+f"(d[72]),"+f"(d[73]),"+f"(d[74]),"+f"(d[75]),"+f"(d[76]),"+f"(d[77]),"+f"(d[78]),"+f"(d[79]),"+f"(d[80]),"+f"(d[81]),"+f"(d[82]),"+f"(d[83]),"+f"(d[84]),"+f"(d[85]),"+f"(d[86]),"+f"(d[87]),"+f"(d[88]),"+f"(d[89]),"+f"(d[90]),"+f"(d[91]),"+f"(d[92]),"+f"(d[93]),"+f"(d[94]),"+f"(d[95])
      : "l"(da), "l"(db), "r"(sd));
}
template<> __device__ __forceinline__ void mma_ssp<200>(float* d, uint64_t da, uint64_t db, int sd) {
    asm volatile("{\n.reg .pred p;\nsetp.ne.b32 p, %102, 0;\nwgmma.mma_async.sync.aligned.m64n200k16.f32.bf16.bf16 {%0,%1,%2,%3,%4,%5,%6,%7,%8,%9,%10,%11,%12,%13,%14,%15,%16,%17,%18,%19,%20,%21,%22,%23,%24,%25,%26,%27,%28,%29,%30,%31,%32,%33,%34,%35,%36,%37,%38,%39,%40,%41,%42,%43,%44,%45,%46,%47,%48,%49,%50,%51,%52,%53,%54,%55,%56,%57,%58,%59,%60,%61,%62,%63,%64,%65,%66,%67,%68,%69,%70,%71,%72,%73,%74,%75,%76,%77,%78,%79,%80,%81,%82,%83,%84,%85,%86,%87,%88,%89,%90,%91,%92,%93,%94,%95,%96,%97,%98,%99}, %100, %101, p, 1, 1, 0, 1;\n}\n"
      : "+f"(d[0]),"+f"(d[1]),"+f"(d[2]),"+f"(d[3]),"+f"(d[4]),"+f"(d[5]),"+f"(d[6]),"+f"(d[7]),"+f"(d[8]),"+f"(d[9]),"+f"(d[10]),"+f"(d[11]),"+f"(d[12]),"+f"(d[13]),"+f"(d[14]),"+f"(d[15]),"+f"(d[16]),"+f"(d[17]),"+f"(d[18]),"+f"(d[19]),"+f"(d[20]),"+f"(d[21]),"+f"(d[22]),"+f"(d[23]),"+f"(d[24]),"+f"(d[25]),"+f"(d[26]),"+f"(d[27]),"+f"(d[28]),"+f"(d[29]),"+f"(d[30]),"+f"(d[31]),"+f"(d[32]),"+f"(d[33]),"+f"(d[34]),"+f"(d[35]),"+f"(d[36]),"+f"(d[37]),"+f"(d[38]),"+f"(d[39]),"+f"(d[40]),"+f"(d[41]),"+f"(d[42]),"+f"(d[43]),"+f"(d[44]),"+f"(d[45]),"+f"(d[46]),"+f"(d[47]),"+f"(d[48]),"+f"(d[49]),"+f"(d[50]),"+f"(d[51]),"+f"(d[52]),"+f"(d[53]),"+f"(d[54]),"+f"(d[55]),"+f"(d[56]),"+f"(d[57]),"+f"(d[58]),"+f"(d[59]),"+f"(d[60]),"+f"(d[61]),"+f"(d[62]),"+f"(d[63]),"+f"(d[64]),"+f"(d[65]),"+f"(d[66]),"+f"(d[67]),"+f"(d[68]),"+f"(d[69]),"+f"(d[70]),"+f"(d[71]),"+f"(d[72]),"+f"(d[73]),"+f"(d[74]),"+f"(d[75]),"+f"(d[76]),"+f"(d[77]),"+f"(d[78]),"+f"(d[79]),"+f"(d[80]),"+f"(d[81]),"+f"(d[82]),"+f"(d[83]),"+f"(d[84]),"+f"(d[85]),"+f"(d[86]),"+f"(d[87]),"+f"(d[88]),"+f"(d[89]),"+f"(d[90]),"+f"(d[91]),"+f"(d[92]),"+f"(d[93]),"+f"(d[94]),"+f"(d[95]),"+f"(d[96]),"+f"(d[97]),"+f"(d[98]),"+f"(d[99])
      : "l"(da), "l"(db), "r"(sd));
}
template<int SD> __device__ __forceinline__ void mma_n192_ss(float* d, uint64_t da, uint64_t db) {
    asm volatile("wgmma.mma_async.sync.aligned.m64n192k16.f32.bf16.bf16 {%0,%1,%2,%3,%4,%5,%6,%7,%8,%9,%10,%11,%12,%13,%14,%15,%16,%17,%18,%19,%20,%21,%22,%23,%24,%25,%26,%27,%28,%29,%30,%31,%32,%33,%34,%35,%36,%37,%38,%39,%40,%41,%42,%43,%44,%45,%46,%47,%48,%49,%50,%51,%52,%53,%54,%55,%56,%57,%58,%59,%60,%61,%62,%63,%64,%65,%66,%67,%68,%69,%70,%71,%72,%73,%74,%75,%76,%77,%78,%79,%80,%81,%82,%83,%84,%85,%86,%87,%88,%89,%90,%91,%92,%93,%94,%95}, %96, %97, %98, 1, 1, 0, 1;\n"
      : "+f"(d[0]),"+f"(d[1]),"+f"(d[2]),"+f"(d[3]),"+f"(d[4]),"+f"(d[5]),"+f"(d[6]),"+f"(d[7]),"+f"(d[8]),"+f"(d[9]),"+f"(d[10]),"+f"(d[11]),"+f"(d[12]),"+f"(d[13]),"+f"(d[14]),"+f"(d[15]),"+f"(d[16]),"+f"(d[17]),"+f"(d[18]),"+f"(d[19]),"+f"(d[20]),"+f"(d[21]),"+f"(d[22]),"+f"(d[23]),"+f"(d[24]),"+f"(d[25]),"+f"(d[26]),"+f"(d[27]),"+f"(d[28]),"+f"(d[29]),"+f"(d[30]),"+f"(d[31]),"+f"(d[32]),"+f"(d[33]),"+f"(d[34]),"+f"(d[35]),"+f"(d[36]),"+f"(d[37]),"+f"(d[38]),"+f"(d[39]),"+f"(d[40]),"+f"(d[41]),"+f"(d[42]),"+f"(d[43]),"+f"(d[44]),"+f"(d[45]),"+f"(d[46]),"+f"(d[47]),"+f"(d[48]),"+f"(d[49]),"+f"(d[50]),"+f"(d[51]),"+f"(d[52]),"+f"(d[53]),"+f"(d[54]),"+f"(d[55]),"+f"(d[56]),"+f"(d[57]),"+f"(d[58]),"+f"(d[59]),"+f"(d[60]),"+f"(d[61]),"+f"(d[62]),"+f"(d[63]),"+f"(d[64]),"+f"(d[65]),"+f"(d[66]),"+f"(d[67]),"+f"(d[68]),"+f"(d[69]),"+f"(d[70]),"+f"(d[71]),"+f"(d[72]),"+f"(d[73]),"+f"(d[74]),"+f"(d[75]),"+f"(d[76]),"+f"(d[77]),"+f"(d[78]),"+f"(d[79]),"+f"(d[80]),"+f"(d[81]),"+f"(d[82]),"+f"(d[83]),"+f"(d[84]),"+f"(d[85]),"+f"(d[86]),"+f"(d[87]),"+f"(d[88]),"+f"(d[89]),"+f"(d[90]),"+f"(d[91]),"+f"(d[92]),"+f"(d[93]),"+f"(d[94]),"+f"(d[95])
      : "l"(da), "l"(db), "n"(SD));
}
template<int SD> __device__ __forceinline__ void mma_n64_ss(float* d, uint64_t da, uint64_t db) {
    asm volatile("wgmma.mma_async.sync.aligned.m64n64k16.f32.bf16.bf16 {%0,%1,%2,%3,%4,%5,%6,%7,%8,%9,%10,%11,%12,%13,%14,%15,%16,%17,%18,%19,%20,%21,%22,%23,%24,%25,%26,%27,%28,%29,%30,%31}, %32, %33, %34, 1, 1, 0, 1;\n"
      : "+f"(d[0]),"+f"(d[1]),"+f"(d[2]),"+f"(d[3]),"+f"(d[4]),"+f"(d[5]),"+f"(d[6]),"+f"(d[7]),"+f"(d[8]),"+f"(d[9]),"+f"(d[10]),"+f"(d[11]),"+f"(d[12]),"+f"(d[13]),"+f"(d[14]),"+f"(d[15]),"+f"(d[16]),"+f"(d[17]),"+f"(d[18]),"+f"(d[19]),"+f"(d[20]),"+f"(d[21]),"+f"(d[22]),"+f"(d[23]),"+f"(d[24]),"+f"(d[25]),"+f"(d[26]),"+f"(d[27]),"+f"(d[28]),"+f"(d[29]),"+f"(d[30]),"+f"(d[31])
      : "l"(da), "l"(db), "n"(SD));
}
template<int SD> __device__ __forceinline__ void mma_n128_ss(float* d, uint64_t da, uint64_t db) {
    asm volatile("wgmma.mma_async.sync.aligned.m64n128k16.f32.bf16.bf16 {%0,%1,%2,%3,%4,%5,%6,%7,%8,%9,%10,%11,%12,%13,%14,%15,%16,%17,%18,%19,%20,%21,%22,%23,%24,%25,%26,%27,%28,%29,%30,%31,%32,%33,%34,%35,%36,%37,%38,%39,%40,%41,%42,%43,%44,%45,%46,%47,%48,%49,%50,%51,%52,%53,%54,%55,%56,%57,%58,%59,%60,%61,%62,%63}, %64, %65, %66, 1, 1, 0, 1;\n"
      : "+f"(d[0]),"+f"(d[1]),"+f"(d[2]),"+f"(d[3]),"+f"(d[4]),"+f"(d[5]),"+f"(d[6]),"+f"(d[7]),"+f"(d[8]),"+f"(d[9]),"+f"(d[10]),"+f"(d[11]),"+f"(d[12]),"+f"(d[13]),"+f"(d[14]),"+f"(d[15]),"+f"(d[16]),"+f"(d[17]),"+f"(d[18]),"+f"(d[19]),"+f"(d[20]),"+f"(d[21]),"+f"(d[22]),"+f"(d[23]),"+f"(d[24]),"+f"(d[25]),"+f"(d[26]),"+f"(d[27]),"+f"(d[28]),"+f"(d[29]),"+f"(d[30]),"+f"(d[31]),"+f"(d[32]),"+f"(d[33]),"+f"(d[34]),"+f"(d[35]),"+f"(d[36]),"+f"(d[37]),"+f"(d[38]),"+f"(d[39]),"+f"(d[40]),"+f"(d[41]),"+f"(d[42]),"+f"(d[43]),"+f"(d[44]),"+f"(d[45]),"+f"(d[46]),"+f"(d[47]),"+f"(d[48]),"+f"(d[49]),"+f"(d[50]),"+f"(d[51]),"+f"(d[52]),"+f"(d[53]),"+f"(d[54]),"+f"(d[55]),"+f"(d[56]),"+f"(d[57]),"+f"(d[58]),"+f"(d[59]),"+f"(d[60]),"+f"(d[61]),"+f"(d[62]),"+f"(d[63])
      : "l"(da), "l"(db), "n"(SD));
}
template<int SD> __device__ __forceinline__ void mma_n64_rs(float* d, uint32_t a0, uint32_t a1, uint32_t a2, uint32_t a3, uint64_t db) {
    asm volatile("wgmma.mma_async.sync.aligned.m64n64k16.f32.bf16.bf16 {%0,%1,%2,%3,%4,%5,%6,%7,%8,%9,%10,%11,%12,%13,%14,%15,%16,%17,%18,%19,%20,%21,%22,%23,%24,%25,%26,%27,%28,%29,%30,%31}, {%32,%33,%34,%35}, %36, %37, 1, 1, 0;\n"
      : "+f"(d[0]),"+f"(d[1]),"+f"(d[2]),"+f"(d[3]),"+f"(d[4]),"+f"(d[5]),"+f"(d[6]),"+f"(d[7]),"+f"(d[8]),"+f"(d[9]),"+f"(d[10]),"+f"(d[11]),"+f"(d[12]),"+f"(d[13]),"+f"(d[14]),"+f"(d[15]),"+f"(d[16]),"+f"(d[17]),"+f"(d[18]),"+f"(d[19]),"+f"(d[20]),"+f"(d[21]),"+f"(d[22]),"+f"(d[23]),"+f"(d[24]),"+f"(d[25]),"+f"(d[26]),"+f"(d[27]),"+f"(d[28]),"+f"(d[29]),"+f"(d[30]),"+f"(d[31])
      : "r"(a0), "r"(a1), "r"(a2), "r"(a3), "l"(db), "n"(SD));
}
template<int SD> __device__ __forceinline__ void mma_n64_sk(float* d, uint64_t da, uint64_t db) {
    asm volatile("wgmma.mma_async.sync.aligned.m64n64k16.f32.bf16.bf16 {%0,%1,%2,%3,%4,%5,%6,%7,%8,%9,%10,%11,%12,%13,%14,%15,%16,%17,%18,%19,%20,%21,%22,%23,%24,%25,%26,%27,%28,%29,%30,%31}, %32, %33, %34, 1, 1, 0, 0;\n"
      : "+f"(d[0]),"+f"(d[1]),"+f"(d[2]),"+f"(d[3]),"+f"(d[4]),"+f"(d[5]),"+f"(d[6]),"+f"(d[7]),"+f"(d[8]),"+f"(d[9]),"+f"(d[10]),"+f"(d[11]),"+f"(d[12]),"+f"(d[13]),"+f"(d[14]),"+f"(d[15]),"+f"(d[16]),"+f"(d[17]),"+f"(d[18]),"+f"(d[19]),"+f"(d[20]),"+f"(d[21]),"+f"(d[22]),"+f"(d[23]),"+f"(d[24]),"+f"(d[25]),"+f"(d[26]),"+f"(d[27]),"+f"(d[28]),"+f"(d[29]),"+f"(d[30]),"+f"(d[31])
      : "l"(da), "l"(db), "n"(SD));
}
template<int SD> __device__ __forceinline__ void mma_n24_rs(float* d, uint32_t a0, uint32_t a1, uint32_t a2, uint32_t a3, uint64_t db) {
    asm volatile("wgmma.mma_async.sync.aligned.m64n24k16.f32.bf16.bf16 {%0,%1,%2,%3,%4,%5,%6,%7,%8,%9,%10,%11}, {%12,%13,%14,%15}, %16, %17, 1, 1, 1;\n"
      : "+f"(d[0]),"+f"(d[1]),"+f"(d[2]),"+f"(d[3]),"+f"(d[4]),"+f"(d[5]),"+f"(d[6]),"+f"(d[7]),"+f"(d[8]),"+f"(d[9]),"+f"(d[10]),"+f"(d[11])
      : "r"(a0), "r"(a1), "r"(a2), "r"(a3), "l"(db), "n"(SD));
}

__host__ __device__ constexpr uint64_t mkdesc(uint32_t addr, uint32_t lbo, uint32_t sbo, uint32_t swz) {
    return (uint64_t)((addr & 0x3FFFF) >> 4) | ((uint64_t)(lbo >> 4) << 16) | ((uint64_t)(sbo >> 4) << 32) | ((uint64_t)swz << 62);
}
#define WG_FENCE() asm volatile("wgmma.fence.sync.aligned;" ::: "memory")
#define WG_COMMIT() asm volatile("wgmma.commit_group.sync.aligned;" ::: "memory")
#define WG_WAIT(n) asm volatile("wgmma.wait_group.sync.aligned " #n ";" ::: "memory")
template<int N> __device__ __forceinline__ void keep(float* r) {
#pragma unroll
    for (int i = 0; i < N; i++) asm volatile("" : "+f"(r[i]) :: "memory");
}
template<int N> __device__ __forceinline__ void kill(float* r) {
#pragma unroll
    for (int i = 0; i < N; i++) asm volatile("" : "=f"(r[i]));
}
template<int N> __device__ __forceinline__ void keep(uint32_t* r) {
#pragma unroll
    for (int i = 0; i < N; i++) asm volatile("" : "+r"(r[i]) :: "memory");
}
__device__ __forceinline__ uint32_t cl(uint32_t a) { return a + ((blockIdx.x & 1) << 24); }
__device__ __forceinline__ void mbar_init(uint32_t a, uint32_t c) { asm volatile("mbarrier.init.shared::cta.b64 [%0], %1;" :: "r"(cl(a)), "r"(c) : "memory"); }
__device__ __forceinline__ void mbar_arrive(uint32_t a) { asm volatile("mbarrier.arrive.shared::cta.b64 _, [%0];" :: "r"(cl(a)) : "memory"); }
__device__ __forceinline__ void mbar_wait(uint32_t a, uint32_t ph) {
    asm volatile("{\n.reg .pred p, q;\n.reg .u32 n;\nmov.u32 n, 0;\n"
        "LW:\nmbarrier.try_wait.parity.shared::cta.b64 p, [%0], %1;\n@p bra LD;\n"
        "add.u32 n, n, 1;\nsetp.gt.u32 q, n, 2000000;\n@q trap;\nbra LW;\nLD:\n}" :: "r"(cl(a)), "r"(ph) : "memory");
}
__device__ __forceinline__ void mbar_wait_raw(uint32_t addr, uint32_t ph) {
    asm volatile("{\n.reg .pred p, q;\n.reg .u32 n;\nmbarrier.try_wait.parity.shared::cta.b64 p, [%0], %1;\n@p bra LD;\nmov.u32 n, 0;\n"
        "LW:\nmbarrier.try_wait.parity.shared::cta.b64 p, [%0], %1;\n@p bra LD;\n"
        "add.u32 n, n, 1;\nsetp.gt.u32 q, n, 2000000;\n@q trap;\nbra LW;\nLD:\n}" :: "r"(addr), "r"(ph) : "memory");
}
__device__ __forceinline__ void flag_wait(const unsigned* p, unsigned target) {
    asm volatile("{\n.reg .pred p, q;\n.reg .u32 n, v;\nmov.u32 n, 0;\n"
        "LW:\nld.acquire.gpu.global.u32 v, [%0];\nsub.u32 v, v, %1;\nsetp.ge.s32 p, v, 0;\n@p bra LD;\n"
        "nanosleep.u32 100;\nadd.u32 n, n, 1;\nsetp.gt.u32 q, n, 4000000;\n@q trap;\nbra LW;\nLD:\n}" :: "l"(p), "r"(target) : "memory");
}
__device__ __forceinline__ void red_release(unsigned* p, unsigned v) { asm volatile("red.release.gpu.global.add.u32 [%0], %1;" :: "l"(p), "r"(v) : "memory"); }
__device__ __forceinline__ void red_relaxed(unsigned* p, unsigned v) { asm volatile("red.relaxed.gpu.global.add.u32 [%0], %1;" :: "l"(p), "r"(v) : "memory"); }
__device__ __forceinline__ void st_release(unsigned* p, unsigned v) { asm volatile("st.release.gpu.global.u32 [%0], %1;" :: "l"(p), "r"(v) : "memory"); }
__device__ __forceinline__ unsigned ld_relaxed(const unsigned* p) { unsigned v; asm volatile("ld.relaxed.gpu.global.u32 %0, [%1];" : "=r"(v) : "l"(p) : "memory"); return v; }
__device__ __forceinline__ unsigned ld_acquire(const unsigned* p) { unsigned v; asm volatile("ld.acquire.gpu.global.u32 %0, [%1];" : "=r"(v) : "l"(p) : "memory"); return v; }
__device__ __forceinline__ unsigned get_tag() { return ld_relaxed(&g_done) / (4 * NCTA) + 1; }
__device__ __forceinline__ unsigned long long ld_tagged(const unsigned long long* p) {
    unsigned long long v; asm volatile("ld.relaxed.gpu.global.b64 %0, [%1];" : "=l"(v) : "l"(p) : "memory"); return v;
}
__device__ __forceinline__ void fence_async() { asm volatile("fence.proxy.async;" ::: "memory"); }
__device__ __forceinline__ void bar_sync(int id, int n) { asm volatile("bar.sync %0, %1;" :: "r"(id), "r"(n) : "memory"); }
__device__ __forceinline__ void bar_arrive(int id, int n) { asm volatile("bar.arrive %0, %1;" :: "r"(id), "r"(n) : "memory"); }
#define ELECT_BEGIN "{\n.reg .pred p, e;\nelect.sync _|p, 0xffffffff;\nsetp.ne.and.u32 e, %1, 0, p;\n@e mbarrier.arrive.expect_tx.shared::cta.b64 _, [%0], %1;\n"
__device__ __forceinline__ void bulk_load(uint32_t dst, const void* src, uint32_t bytes, uint32_t bar, uint32_t tx) {
    asm volatile(ELECT_BEGIN ".reg .b64 pol;\ncreatepolicy.fractional.L2::evict_first.b64 pol, 1.0;\n@p cp.async.bulk.shared::cluster.global.mbarrier::complete_tx::bytes.L2::cache_hint [%2], [%3], %4, [%0], pol;\n}"
        :: "r"(cl(bar)), "r"(tx), "r"(cl(dst)), "l"(src), "r"(bytes) : "memory");
}
__device__ __forceinline__ void send_half(int kb) {
    const uint32_t off = A_OFF + (blockIdx.x & 1) * 8192 + kb * 16384, peer = ((blockIdx.x & 1) ^ 1) << 24;
    asm volatile(ELECT_BEGIN "@p cp.async.bulk.shared::cluster.shared::cta.mbarrier::complete_tx::bytes [%2], [%3], 8192, [%4];\n}"
        :: "r"(cl(BAR_FULLA + 8 * kb)), "r"(8192), "r"(off + peer), "r"(cl(off)), "r"(BAR_FULLA + 8 * kb + peer) : "memory");
}
__device__ __forceinline__ void tma2d(uint32_t dst, const CUtensorMap* m, int c0, int c1, uint32_t bar, uint32_t tx) {
    asm volatile(ELECT_BEGIN "@p cp.async.bulk.tensor.2d.shared::cluster.global.mbarrier::complete_tx::bytes [%2], [%3, {%4, %5}], [%0];\n}"
        :: "r"(cl(bar)), "r"(tx), "r"(cl(dst)), "l"(m), "r"(c0), "r"(c1) : "memory");
}
__device__ __forceinline__ void tma3d(uint32_t dst, const CUtensorMap* m, int c1, int c2, uint32_t bar, uint32_t tx) {
    asm volatile(ELECT_BEGIN "@p cp.async.bulk.tensor.3d.shared::cluster.global.mbarrier::complete_tx::bytes [%2], [%3, {%6, %4, %5}], [%0];\n}"
        :: "r"(cl(bar)), "r"(tx), "r"(cl(dst)), "l"(m), "r"(c1), "r"(c2), "r"(0) : "memory");
}
__device__ __forceinline__ void tma5d(uint32_t dst, const CUtensorMap* m, int c3, int c4, uint32_t bar, uint32_t tx) {
    asm volatile(ELECT_BEGIN "@p cp.async.bulk.tensor.5d.shared::cluster.global.mbarrier::complete_tx::bytes [%2], [%3, {%6, %6, %6, %4, %5}], [%0];\n}"
        :: "r"(cl(bar)), "r"(tx), "r"(cl(dst)), "l"(m), "r"(c3), "r"(c4), "r"(0) : "memory");
}
__device__ __forceinline__ uint32_t pack_bf16(float lo, float hi) {
    uint32_t r; asm("cvt.rn.bf16x2.f32 %0, %1, %2;" : "=r"(r) : "f"(hi), "f"(lo)); return r;
}
__device__ __forceinline__ float bf_lo(uint32_t v) { return __uint_as_float(v << 16); }
__device__ __forceinline__ float bf_hi(uint32_t v) { return __uint_as_float(v & 0xffff0000u); }
__device__ __forceinline__ float2 lds64(uint32_t a) { float2 v; asm volatile("ld.shared.v2.f32 {%0,%1}, [%2];" : "=f"(v.x), "=f"(v.y) : "r"(cl(a))); return v; }
__device__ __forceinline__ uint32_t lds32(uint32_t a) { uint32_t v; asm volatile("ld.shared.u32 %0, [%1];" : "=r"(v) : "r"(cl(a)) : "memory"); return v; }
__device__ __forceinline__ void l2_prefetch(const void* p, uint32_t bytes, uint32_t pause) {
#pragma unroll 1
    for (uint32_t o = (threadIdx.x & 31) * 128; o < bytes; o += 4096) {
        asm volatile("prefetch.global.L2 [%0];" :: "l"((const uint8_t*)p + o) : "memory");
        if (pause) asm volatile("nanosleep.u32 %0;" :: "r"(pause));
    }
    __syncwarp();
}
__device__ __forceinline__ float ex2(float x) { float y; asm("ex2.approx.ftz.f32 %0, %1;" : "=f"(y) : "f"(x)); return y; }

__device__ __forceinline__ int cta_m() { return blockIdx.x >> 3; }
__device__ __forceinline__ int cta_j() { return blockIdx.x & 7; }
__device__ __forceinline__ bool cta_isG() { return blockIdx.x < 128 && (blockIdx.x & 7) < 3; }
#define AORDER 0x42310000
__device__ __forceinline__ int cta_aidx() {
    const int j = blockIdx.x & 7;
    return blockIdx.x >= 128 ? blockIdx.x - 128 : 4 + ((AORDER >> (4 * j)) & 7) * 16 + (blockIdx.x >> 3);
}

#define MINIW 0x02022000
__device__ __forceinline__ int mini_w() { return (MINIW >> (4 * cta_j())) & 3; }
__device__ __forceinline__ int has_mini() { return mini_w() != 0; }
__device__ __forceinline__ int num_jobs() { return has_mini() + (cta_isG() ? 4 : 2); }
__device__ __forceinline__ int job_id(int q) {
    const int w = q - has_mini(), j = cta_j();
    const uint32_t below = MINIW & ((1u << (4 * j)) - 1);
    return w < 0 ? __popc(below & 0x11111111u) + 2 * __popc(below & 0x22222222u) : 6 + (w < 2 ? 8 * w + j : 10 + 3 * w + j);
}
__device__ __forceinline__ int job_chunk(int id) { return id < 6 ? id : 3 * id - 12; }
__device__ __forceinline__ int job_bar(int q) { return q < 3 ? 11 + q : (q == 3 ? 15 : 3); }

template<int J>
__device__ __forceinline__ void qkv_mainloop(uint32_t* v, int wg, bool elect) {
    constexpr int O = (216 * J) % 64, N1 = 64 - O, N2 = 152 + O, NCH = (O + 216 + 63) / 64, NST = NCH == 4 ? 9 : 7;
    constexpr uint64_t dB = mkdesc(B_OFF, 2048, 1024, 1);
    const uint64_t dA = mkdesc(A_OFF, 16, 1024, 1) + (uint64_t)((wg - 1) * (8192 >> 4));
    int st = NST == 7 ? 6 : 0; uint32_t ph = 0;
    float acc[108];
#pragma unroll 1
    for (int ks = 0; ks < 36; ks += 2) {
        int st1 = st + 1; uint32_t ph1 = ph; if (st1 == NST) { st1 = 0; ph1 ^= 1; }
        if ((ks & 3) == 0 && ((wg ^ blockIdx.x) & 1) == 0) mbar_wait(BAR_FULLA + 2 * ks, 0);
        mbar_wait(BAR_FULLW + 8 * st, ph);
        mbar_wait(BAR_FULLW + 8 * st1, ph1);
        const uint64_t a = dA + (uint64_t)((ks >> 2) * (16384 >> 4) + (ks & 3) * 2);
        WG_FENCE();
#pragma unroll
        for (int k = 0; k < 2; k++) {
            const uint64_t b = dB + (uint64_t)((k ? st1 : st) * (NCH * 2048 >> 4));
            if (N2 <= 200) mma_ssp<(N2 <= 200 ? N2 : 128)>(acc + N1 / 2, a + 2 * k, b + (2048 >> 4), ks + k);
            else { mma_ssp<128>(acc + N1 / 2, a + 2 * k, b + (2048 >> 4), ks + k); mma_ssp<80>(acc + N1 / 2 + 64, a + 2 * k, b + (6144 >> 4), ks + k); }
            mma_ssp<N1>(acc, a + 2 * k, b + (2 * O >> 4), ks + k);
        }
        WG_COMMIT();
        WG_WAIT(1);
        if ((threadIdx.x & 127) < 2 && ks > 0) {
            int sp = st - 1 - (threadIdx.x & 1); if (sp < 0) sp += NST;
            mbar_arrive(BAR_EMPTYW + 8 * sp);
        }
        st = st1 + 1; ph = ph1; if (st == NST) { st = 0; ph ^= 1; }
    }
    WG_WAIT(0);
    keep<108>(acc);
    if ((threadIdx.x & 127) < 3) mbar_arrive((threadIdx.x & 127) == 2 ? BAR_WDONE : BAR_EMPTYW + 8 * (NST - 1 - (threadIdx.x & 1)));
    if (wg == 1) TS(16);
    constexpr float QS = 0.23570226f * 1.44269504f;
#pragma unroll
    for (int i = 0; i < 54; i++) v[i] = 216 * J + 8 * (i >> 1) < DM ? pack_bf16(acc[2 * i] * QS, acc[2 * i + 1] * QS) : pack_bf16(acc[2 * i], acc[2 * i + 1]);
}

__device__ __forceinline__ uint64_t sel_desc(int q) { return mkdesc(ONE_OFF, 0, 0, 0) + (uint64_t)(q * (128 >> 4)) + ((uint64_t)((6 - q) * (128 >> 4)) << 16); }
constexpr uint64_t SEL2 = (uint64_t)(128 >> 4) << 16;
constexpr uint64_t BIAS_DESC = mkdesc(BIAS_OFF, 1024, 0, 1);
template<int W>
__device__ __forceinline__ void mini_mainloop(float* acc0, float* acc1, bool elect) {
    constexpr uint64_t dA = mkdesc(A_OFF, 16, 1024, 1), dB = mkdesc(B_OFF, 6144, 1024, 1);
    WG_FENCE();
    if (W == 1) { mma_n64_ss<0>(acc0, sel_desc(0), BIAS_DESC); mma_n64_ss<0>(acc1, sel_desc(0) + SEL2, BIAS_DESC); }
    else { mma_n128_ss<0>(acc0, sel_desc(0), BIAS_DESC); mma_n128_ss<0>(acc1, sel_desc(0) + SEL2, BIAS_DESC); }
    WG_COMMIT();
    int st = 0;
#pragma unroll 1
    for (int s = 0; s < 6 * W; s++) {
        mbar_wait(BAR_FULLB + 8 * st, s >= 6);
        if (s == 6 * W - 1) bar_arrive(9, 256);
        WG_FENCE();
#pragma unroll
        for (int k = 0; k < 6 / W; k++) {
            const int ks = (6 / W) * s + k;
            const uint64_t a = dA + (uint64_t)((ks >> 2) * (16384 >> 4) + (ks & 3) * 2), b = dB + (uint64_t)(st * (12288 >> 4) + k * (2048 >> 4));
            if (W == 1) { mma_n64_ss<1>(acc0, a, b); mma_n64_ss<1>(acc1, a + (8192 >> 4), b); }
            else { mma_n128_ss<1>(acc0, a, b); mma_n128_ss<1>(acc1, a + (8192 >> 4), b); }
        }
        WG_COMMIT();
        WG_WAIT(1);
        if (elect && s > 0) mbar_arrive(BAR_EMPTYB + 8 * (st == 0 ? 5 : st - 1));
        if (++st == 6) st = 0;
    }
    WG_WAIT(0);
    if (elect) mbar_arrive(BAR_EMPTYB + 8 * 5);
    keep<32 * W>(acc0); keep<32 * W>(acc1);
}
__device__ __forceinline__ void job_mainloop(float* acc0, float* acc1, int q, bool g2, uint32_t xa, bool elect) {
    constexpr uint64_t dB = mkdesc(B_OFF, 4096, 1024, 1);
    const bool last = q == num_jobs() - 1, releaseA = g2 || last, handoff = !g2 && (!last || cta_isG());
    WG_FENCE();
    mma_n192_ss<0>(acc0, sel_desc(g2 ? 5 : q), BIAS_DESC); mma_n192_ss<0>(acc1, sel_desc(g2 ? 5 : q) + SEL2, BIAS_DESC);
    WG_COMMIT();
    if (q > 0) bar_sync(8 + (q & 1), 256);
    const int nturn = g2 ? 27 : 3;
    int grp = 0; uint32_t pa = 1;
#pragma unroll 1
    for (int u = 0; u < nturn; u++) {
        const uint32_t par = (q + u + (mini_w() >> 1)) & 1;
        if (g2 && (u == 3 || u == 12 || u == 24)) TS2(u == 3 ? 4 : (u == 12 ? 5 : 6));
        if (u == 24) {
            mbar_wait(BAR_FULLA, pa); mbar_wait(BAR_FULLA + 8, pa); mbar_wait(BAR_FULLA + 16, pa);
            WG_WAIT(0);
            keep<96>(acc0); keep<96>(acc1);
            if (elect) { mbar_arrive(BAR_EMPTYB + 8 * 5); mbar_arrive(BAR_EMPTYA + 8 * 8); }
#pragma unroll
            for (int i2 = 0; i2 < 12; i2++) {
#pragma unroll
                for (int mh = 0; mh < 2; mh++) {
                    float* a = (mh ? acc1 : acc0) + 8 * i2;
                    uint32_t r[4];
                    asm volatile("ldmatrix.sync.aligned.m8n8.x4.shared.b16 {%0,%1,%2,%3}, [%4];" : "=r"(r[0]), "=r"(r[1]), "=r"(r[2]), "=r"(r[3])
                        : "r"(cl((xa ^ ((i2 & 3) << 5)) + (i2 >> 2) * 16384 + mh * 8192)) : "memory");
#pragma unroll
                    for (int e = 0; e < 4; e++) { a[2 * e] = fmaf(a[2 * e], 0.5f, bf_lo(r[e])); a[2 * e + 1] = fmaf(a[2 * e + 1], 0.5f, bf_hi(r[e])); }
                }
            }
            keep<96>(acc0); keep<96>(acc1);
            grp = 1;
        }
        const uint64_t dAu = (!g2 ? mkdesc(A_OFF, 16, 1024, 1) : (u < 24 ? mkdesc(A_OFF, 16, 512, 2) : mkdesc(A_OFF, 128, 1024, 0))) + (uint64_t)(grp * (3 * 16384 >> 4));
        const uint32_t kst = u >= 24 ? (256 >> 4) : (32 >> 4), hst = !g2 ? (64 >> 4) : (u < 24 ? (8192 >> 4) : (512 >> 4)), mst = (g2 && u < 24) ? (4096 >> 4) : (8192 >> 4);
#pragma unroll
        for (int st = 0; st < 6; st++) {
            const int kb = st >> 1, half = st & 1;
            if (half == 0 && g2) mbar_wait(BAR_FULLA + 8 * (3 * grp + kb), pa);
            mbar_wait(BAR_FULLB + 8 * st, par);
            if (st == 5 && u == 2 && handoff) bar_arrive(8 + ((q + 1) & 1), 256);
            WG_FENCE();
#pragma unroll
            for (int k = 0; k < 2; k++) {
                const uint64_t a = dAu + (uint64_t)(kb * (16384 >> 4) + half * hst + k * kst);
                const uint64_t b = dB + (uint64_t)((st * 12288 + k * 2048) >> 4);
                mma_n192_ss<1>(acc0, a, b); mma_n192_ss<1>(acc1, a + mst, b);
            }
            WG_COMMIT();
            WG_WAIT(1);
            if (elect && (st > 0 || u > 0)) {
                if (st > 0 || u != 24) {
                    mbar_arrive(BAR_EMPTYB + 8 * ((st + 5) % 6));
                    if (half == 0 && releaseA) mbar_arrive(BAR_EMPTYA + 8 * (kb == 0 && grp == 0 ? 8 : 3 * grp + kb - 1));
                }
                if (st == 1 && u == 24) { mbar_arrive(BAR_EMPTYA); mbar_arrive(BAR_EMPTYA + 8); mbar_arrive(BAR_EMPTYA + 16); }
            }
        }
        if (++grp == 3) { grp = 0; pa ^= 1; }
    }
    WG_WAIT(0);
    if (elect && !g2) { mbar_arrive(BAR_EMPTYB + 8 * 5); if (releaseA) mbar_arrive(BAR_EMPTYA + 8 * 8); }
    keep<96>(acc0); keep<96>(acc1);
}

__device__ __forceinline__ void epilogue_gelu(const float* acc, uint8_t* hp, int nchunk) {
#pragma unroll
    for (int i4 = 0; i4 < 6; i4++) {
        if ((i4 == 2 || i4 == 4) && i4 == 2 * nchunk) break;
        float z[16];
#define XX(e) acc[4 * (8 * (i4 >> 1) + (i4 & 1) + 2 * ((e) >> 2)) + ((e) & 3)]
#pragma unroll
        for (int e = 0; e < 16; e++) z[e] = XX(e) * fmaf(XX(e) * XX(e), 0.035677408f, 0.79788456f);
#pragma unroll
        for (int e = 0; e < 16; e++) asm("tanh.approx.f32 %0, %0;" : "+f"(z[e]));
#pragma unroll
        for (int e = 0; e < 16; e++) z[e] = fmaf(XX(e), z[e], XX(e));
#undef XX
#pragma unroll
        for (int r = 0; r < 2; r++)
            *(uint4*)(hp + r * 512 + i4 * 8192) = make_uint4(pack_bf16(z[2 * r], z[2 * r + 1]), pack_bf16(z[4 + 2 * r], z[5 + 2 * r]),
                                                                         pack_bf16(z[8 + 2 * r], z[9 + 2 * r]), pack_bf16(z[12 + 2 * r], z[13 + 2 * r]));
    }
}
__device__ __forceinline__ void job_epilogue(float* acc0, float* acc1, int q, int warp, int g, int t) {
    uint8_t* hp = g_h + (size_t)(cta_m() * 72 + job_chunk(job_id(q))) * 16384 + warp * 1024 + g * 64 + ((t ^ (g >> 1)) << 4);
    epilogue_gelu(acc0, hp, q < has_mini() ? mini_w() : 3);
    epilogue_gelu(acc1, hp + 4096, q < has_mini() ? mini_w() : 3);
    kill<96>(acc0); kill<96>(acc1);
    bar_arrive(job_bar(q), 160);
}

__device__ __forceinline__ void epilogue_qkv(const uint32_t* vv, int rg, int g, int t, int wg) {
    const int j = cta_j();
#define V(r, i) vv[2 * (i) + (r)]
    if (wg == 2 && !has_mini()) bar_sync(14, 256);
    uint8_t* p = g_qkv + (size_t)(12 * j) * 98304 + rg * 384 + g * 16;
    uint8_t* pr[4];
#pragma unroll
    for (int k = 0; k < 4; k++) { const int r = (t - k) & 3; pr[k] = p + (r >> 1) * 128 + (r & 1) * 8; asm volatile("" : "+l"(pr[k])); }
    uint8_t* p3 = p + t * 98304 + 256;
    asm volatile("" : "+l"(p3));
    const uint32_t pk0 = ((POLYMASK >> (rg & 15)) & 1) ? 0x3f803f80u : 0u, pk1 = ((POLYMASK >> ((rg + 1) & 15)) & 1) ? 0x3f803f80u : 0u;
#pragma unroll
    for (int gi = 0; gi < 3; gi++) {
        const int which = (3 * j + gi) >> 3;
        const uint32_t ec = which == 2 ? 0x00003f80u : 0x427e4740u, ed = which == 2 ? 0u : 0x3aacbe9au, hs = which == 0 ? 0x3f003f00u : 0x3f803f80u;
#pragma unroll
        for (int r = 0; r < 2; r++) {
            const uint32_t a = (t & 1) ? V(r, 9 * gi + 4) : V(r, 9 * gi + 2), b = (t & 1) ? V(r, 9 * gi + 8) : V(r, 9 * gi + 6), pk = r ? pk1 : pk0;
            uint32_t u;
            asm("mul.rn.bf16x2 %0, %1, %2;" : "=r"(u) : "r"((t & 2) ? b : a), "r"(hs));
            *(uint4*)(p3 + 4 * gi * 98304 + r * 384) = make_uint4(u, which == 1 ? pk : ec, which == 1 ? pk : ed, 0u);
        }
        uint32_t mx[2] = {0u, 0u};
#pragma unroll
        for (int h = 4 * gi; h < 4 * gi + 4; h++) {
            {
                const int k = h % 4, i0 = (9 * h) / 4;
                const bool lo = k == 0 || t >= k;
                *(uint2*)(pr[k] + h * 98304) = make_uint2(lo ? V(0, i0) : V(0, i0 + 1), lo ? V(0, i0 + 1) : V(0, i0 + 2));
                *(uint2*)(pr[k] + h * 98304 + 384) = make_uint2(lo ? V(1, i0) : V(1, i0 + 1), lo ? V(1, i0 + 1) : V(1, i0 + 2));
            }
#pragma unroll
            for (int r = 0; r < 2; r++) {
                const int b0 = (9 * h) / 4;
                uint32_t a;
                asm("mul.rn.bf16x2 %0, %1, %1;" : "=r"(a) : "r"(V(r, b0)));
                asm("fma.rn.bf16x2 %0, %1, %1, %0;" : "+r"(a) : "r"(V(r, b0 + 1)));
                asm("fma.rn.bf16x2 %0, %1, %1, %0;" : "+r"(a) : "r"(V(r, b0 + 2)));
                asm("max.NaN.bf16x2 %0, %0, %1;" : "+r"(mx[r]) : "r"(a));
            }
        }
        float w0 = bf_lo(mx[0]) + bf_hi(mx[0]), w1 = bf_lo(mx[1]) + bf_hi(mx[1]);
        w0 += __shfl_xor_sync(0xffffffffu, w0, 1); w1 += __shfl_xor_sync(0xffffffffu, w1, 1);
        w0 += __shfl_xor_sync(0xffffffffu, w0, 2); w1 += __shfl_xor_sync(0xffffffffu, w1, 2);
        const uint32_t bb = __reduce_max_sync(0xffffffffu, max(__float_as_uint(w0) & 0x7fffffffu, __float_as_uint(w1) & 0x7fffffffu));
        if ((threadIdx.x & 31) == 0) asm volatile("red.shared.max.u32 [%0], %1;" :: "r"(cl(BMAX_OFF + 4 * gi)), "r"(bb) : "memory");
    }
}

__device__ __forceinline__ uint32_t exp2_fma(float a, float b, uint32_t c3f00, uint32_t c0003) {
    uint32_t s, m, e, r;
    asm("prmt.b32 %0, %1, %2, 0x5410;" : "=r"(s) : "r"(__float_as_uint(a)), "r"(__float_as_uint(b)));
    asm("lop3.b32 %0, %1, 0x007f007f, %2, 0xEA;" : "=r"(m) : "r"(s), "r"(c3f00));
    asm("lop3.b32 %0, %1, 0xff80ff80, %2, 0xEA;" : "=r"(e) : "r"(s), "r"(c0003));
    asm("fma.rn.bf16x2 %0, %1, %2, %3;" : "=r"(r) : "r"(s), "r"(m), "r"(e));
    return r;
}
template<int B0> __device__ __forceinline__ void exps(const float* S, uint32_t* P, uint32_t c3f00, uint32_t c0003) {
#pragma unroll
    for (int i = 0; i < 4; i++) {
        if ((POLYMASK >> (i + B0)) & 1) { P[2 * i] = exp2_fma(S[4 * i], S[4 * i + 1], c3f00, c0003); P[2 * i + 1] = exp2_fma(S[4 * i + 2], S[4 * i + 3], c3f00, c0003); }
        else { P[2 * i] = pack_bf16(ex2(S[4 * i]), ex2(S[4 * i + 1])); P[2 * i + 1] = pack_bf16(ex2(S[4 * i + 2]), ex2(S[4 * i + 3])); }
    }
}
__device__ __forceinline__ void pv(float* O, const uint32_t* X, const uint32_t* Y, uint64_t dv) {
    mma_n24_rs<1>(O, X[0], X[1], X[2], X[3], dv); mma_n24_rs<1>(O, X[4], X[5], X[6], X[7], dv + (768 >> 4));
    mma_n24_rs<1>(O, Y[0], Y[1], Y[2], Y[3], dv + 2 * (768 >> 4)); mma_n24_rs<1>(O, Y[4], Y[5], Y[6], Y[7], dv + 3 * (768 >> 4));
}
constexpr uint64_t STEP2 = (256 >> 4) - ((uint64_t)(128 >> 4) << 16);
__device__ __forceinline__ void qk(float* S, uint64_t dq, uint64_t dk) {
    mma_n64_sk<0>(S, dq, dk);
    mma_n64_sk<1>(S, dq + STEP2, dk + STEP2);
}
__device__ __forceinline__ void qk_rs(float* S, const uint32_t* q, uint64_t dk) {
    mma_n64_rs<0>(S, q[0], q[1], q[2], q[3], dk);
    mma_n64_rs<1>(S, q[4], q[5], q[6], q[7], dk + STEP2);
}
__device__ __forceinline__ int helper_id() {
    const int j = cta_j(), h = cta_m() + (j == 7 ? 0 : 16);
    return (blockIdx.x < 128 && (j == 7 || j == HELP2) && h < 4 * XS) ? h : -1;
}
__device__ __forceinline__ int num_tasks() { return blockIdx.x >= 128 ? 32 - XS : (helper_id() >= 0 ? 25 : 24); }
__device__ __forceinline__ void seg_info(int seg, int& rd, int& s0, int& len) {
    const int h = helper_id();
    rd = cta_aidx() + NACTA * (h >= 0 ? seg - 1 : seg); s0 = 0; len = 8;
    if (h >= 0 && seg == 0) { rd = 252 + (h & 3); s0 = h >> 2; len = 1; }
    if (rd >= 252 && h < 0) { s0 = XS; len = 8 - XS; }
}
__device__ __forceinline__ void task_table(int task) {
    int seg = task >> 3, k = task & 7;
    if (helper_id() >= 0 && task >= 1) { seg = 1 + ((task - 1) >> 3); k = (task - 1) & 7; }
    int rd, s0, len; seg_info(seg, rd, s0, len);
    const uint32_t hb = (rd >> 3) * 98304;
    asm volatile("st.shared.v2.u32 [%0], {%1, %2};" :: "r"(cl(TASK_OFF + 8 * task)), "r"(hb + 32 * 98304 + (s0 + k) * 12288),
                 "r"(k == 0 ? hb + (rd & 7) * 12288 + 2 + (seg & 1) : 0) : "memory");
}
__device__ __forceinline__ void kv_load(int task) {
    const float2 e = lds64(TASK_OFF + 8 * task);
    const uint32_t ko = __shfl_sync(0xffffffffu, __float_as_uint(e.x), 0), qo = __shfl_sync(0xffffffffu, __float_as_uint(e.y), 0);
    const int sl = task & 7;
    bulk_load(K_OFF + sl * 12288, g_qkv + ko, 12288, BAR_FULLKV + 8 * sl, qo ? 36864 : 24576);
    bulk_load(V_OFF + sl * 12288, g_qkv + ko + 32 * 98304, 12288, BAR_FULLKV + 8 * sl, 0);
    if (qo) bulk_load((qo & 1) ? Q2_OFF : Q_OFF, g_qkv + (qo & ~3u), 12288, BAR_FULLKV + 8 * sl, 0);
}
__device__ __forceinline__ void kv_refill(int task, int wg, int ntask) {
    const int r = task + 8 - KVLAG;
    if ((r & 3) == wg && r >= 8 && r < ntask) {
        mbar_wait(BAR_EMPTYKV + 8 * (r & 7), ((r >> 3) & 1) ^ 1);
        kv_load(r);
    }
}
__device__ __forceinline__ int flag_off(int wg, int stride) { return (wg >> 1) * stride + (wg & 1) * (stride == 64 ? 1 : 8); }
__device__ __forceinline__ void publish_all(unsigned* flag0, int stride, int seg, unsigned tag) {
    mbar_wait(BAR_DEP + 8 * (seg & 1), (seg >> 1) & 1);
    if ((threadIdx.x & 31) < 4) st_release(flag0 + flag_off(threadIdx.x & 31, stride), tag);
    __syncwarp();
}

__device__ __forceinline__ void pieces_acquire(int wg, unsigned tag) {
    const int lane = threadIdx.x & 31, r = blockIdx.x - 128;
    int n = 0;
    while (!__all_sync(0xffffffffu, ld_acquire(&g_pflag[(r * 4 + wg) * 8 + lane % XS]) == tag))
        asm volatile("{\n.reg .pred q;\nnanosleep.u32 100;\nsetp.gt.u32 q, %0, 4000000;\n@q trap;\n}" :: "r"(++n));
#pragma unroll 1
    for (int i = lane; i < XS * 64; i += 32)
        asm volatile("prefetch.global.L2 [%0];" :: "l"(g_part + (r * XS * 4 + (i >> 4)) * 512 + wg * 128 + (i & 15) * 8) : "memory");
}

__device__ __forceinline__ void attention(int wg, unsigned tag) {
    const int lane = threadIdx.x & 31, t = lane & 3;
    const int warp = __shfl_sync(0xffffffffu, (threadIdx.x >> 5) & 3, 0);
    const bool elect = (threadIdx.x & 127) == 0;
    constexpr uint64_t dk0 = mkdesc(K_OFF, 128, 384, 0), dv0 = mkdesc(V_OFF, 384, 128, 0);
    const uint32_t zero = (blockIdx.x >> 20) * lane;
    const uint32_t c3f00 = __shfl_sync(0xffffffffu, 0x3f003f00u + zero, 0);
    const uint32_t c0003 = __shfl_sync(0xffffffffu, 0x00030003u + zero, 0);
    unsigned* pending = nullptr; int pstride = 0;
    const int ntask = num_tasks();
    int T = 0;
#pragma unroll 1
    for (int seg = 0; T < ntask; seg++) {
        int rd, s0, len; seg_info(seg, rd, s0, len);
        const int Tend = T + len, Tpub = (seg > 0 && (seg & 3) == wg && ((warp + wg) & 3) == 2) ? (len < 4 ? Tend - 1 : T + 3) : -1;
        mbar_wait(BAR_FULLKV + 8 * (T & 7), (T >> 3) & 1);
        const bool fast = (__shfl_sync(0xffffffffu, lds32(FAST_OFF), 0) >> (rd >> 5)) & 1;
        const uint64_t q = mkdesc(Q_OFF, 128, 384, 0) + (uint64_t)((((seg & 1) ? Q2_OFF - Q_OFF : 0) + wg * 3072) >> 4);
        float m0 = 0.f, m1 = 0.f;
        float SA[32], SB_[32], O[12];
        uint32_t P[16];
#pragma unroll
        for (int i = 0; i < 12; i++) O[i] = 0.f;
        if (!fast) m0 = m1 = -INFINITY;
        if (len != 8 && len != 1) {
            bar_sync(4 + wg, 128);
            float4 pa[XS][4];
#pragma unroll
            for (int i = 0; i < XS; i++) {
                const float4* pp = g_part + ((rd - 252) * XS + i) * 2048 + threadIdx.x;
#pragma unroll
                for (int e = 0; e < 4; e++) pa[i][e] = __ldcg(pp + 512 * e);
            }
#pragma unroll
            for (int i = 0; i < XS; i++) {
                const float4 a = pa[i][0], b = pa[i][1], c = pa[i][2], m = pa[i][3];
                const float n0 = fmaxf(m0, m.x), n1 = fmaxf(m1, m.y);
                const float f0 = ex2(m0 - n0), f1 = ex2(m1 - n1), g0 = ex2(m.x - n0), g1 = ex2(m.y - n1);
                m0 = n0; m1 = n1;
                O[0] = O[0] * f0 + a.x * g0; O[1] = O[1] * f0 + a.y * g0; O[2] = O[2] * f1 + a.z * g1; O[3] = O[3] * f1 + a.w * g1;
                O[4] = O[4] * f0 + b.x * g0; O[5] = O[5] * f0 + b.y * g0; O[6] = O[6] * f1 + b.z * g1; O[7] = O[7] * f1 + b.w * g1;
                O[8] = O[8] * f0 + c.x * g0; O[9] = O[9] * f0 + c.y * g0; O[10] = O[10] * f1 + c.z * g1; O[11] = O[11] * f1 + c.w * g1;
            }
        }
#pragma unroll
        for (int i = 0; i < 12; i++) asm volatile("add.f32 %0, %0, %1;" : "+f"(O[i]) : "f"(__uint_as_float(zero)) : "memory");
        if (fast) {
            uint64_t dk = dk0 + (uint64_t)((T & 7) * (12288 >> 4)), dv = dv0 + (uint64_t)((T & 7) * (12288 >> 4));
            WG_FENCE();
            qk(SA, q, dk); WG_COMMIT();
            qk(SB_, q, dk + (3072 >> 4)); WG_COMMIT();
            dk += 2 * (3072 >> 4);
            const int role = (warp + wg) & 3;
            const uint32_t duty = role == 0 ? ~0u << (T + 1) : (role == 1 ? 0x11111111u << ((wg + KVLAG) & 3) : (Tpub >= 0 ? 1u << Tpub : (role == 3 && blockIdx.x >= 128 ? 1u << 22 : 0u)));
#pragma unroll 1
            for (; T < Tend; T++) {
                const uint32_t wrap = (T & 7) == 7 ? (8 * 12288 >> 4) : 0;
#pragma unroll
                for (int h = 0; h < 4; h++) {
                    float* S = (h & 1) ? SB_ : SA;
                    WG_WAIT(1);
                    keep<32>(S); keep<12>(O);
                    if (h & 1) { exps<8>(S, P, c3f00, c0003); exps<12>(S + 16, P + 8, c3f00, c0003); } else { exps<0>(S, P, c3f00, c0003); exps<4>(S + 16, P + 8, c3f00, c0003); }
                    keep<16>(P);
                    WG_FENCE();
                    pv(O, P, P + 8, dv); WG_COMMIT();
                    qk(S, q, dk); WG_COMMIT();
                    dv += (3072 >> 4); dk += (3072 >> 4);
                    if (h == 1) { dk -= wrap; if (T + 1 < Tend) mbar_wait_raw(cl(BAR_FULLKV) + 8 * ((T + 1) & 7), ((T + 1) >> 3) & 1); }
                    if (h == 3) dv -= wrap;
                    if (h == 0 && ((duty >> T) & 1)) {
                        if (role == 0) { if (lane == 0) mbar_arrive(BAR_EMPTYKV + 8 * ((T - 1) & 7)); __syncwarp(); }
                        else if (role == 1) kv_refill(T, wg, ntask);
                        else if (role == 2) publish_all(pending, pstride, seg - 1, tag);
                        else pieces_acquire(wg, tag);
                    }
                }
            }
            WG_WAIT(0);
            keep<12>(O); keep<32>(SA); keep<32>(SB_);
            m0 = m1 = 0.f;
        } else {
            const uint32_t qa = ((seg & 1) ? Q2_OFF : Q_OFF) + (wg * 8 + warp * 2) * 384 + lane * 4;
            uint32_t qr[8];
            qr[0] = lds32(qa); qr[1] = lds32(qa + 384); qr[2] = lds32(qa + 128); qr[3] = lds32(qa + 384 + 128);
            qr[4] = lds32(qa + 256 + (t ? 12 - 4 * t : 0)); qr[5] = lds32(qa + 384 + 256 + (t ? 12 - 4 * t : 0));
            qr[6] = lds32(qa + 256 + (t ? 12 - 4 * t : 0)); qr[7] = lds32(qa + 384 + 256 + (t ? 12 - 4 * t : 0));
            keep<8>(qr);
#pragma unroll 1
            for (; T < Tend; T++) {
                if (warp == 1) kv_refill(T, wg, ntask);
                if (T == Tpub) publish_all(pending, pstride, seg - 1, tag);
                if (T == 22 && warp == 3 && blockIdx.x >= 128) pieces_acquire(wg, tag);
                mbar_wait(BAR_FULLKV + 8 * (T & 7), (T >> 3) & 1);
#pragma unroll 1
                for (int h = 0; h < 4; h++) {
                    const uint64_t so = (uint64_t)(((T & 7) * 12288 + h * 3072) >> 4);
                    WG_FENCE();
                    qk_rs(SA, qr, dk0 + so); WG_COMMIT();
                    WG_WAIT(0);
                    keep<32>(SA); keep<12>(O);
                    float n0 = m0, n1 = m1;
#pragma unroll
                    for (int i = 0; i < 8; i++) { n0 = fmaxf(n0, fmaxf(SA[4 * i], SA[4 * i + 1])); n1 = fmaxf(n1, fmaxf(SA[4 * i + 2], SA[4 * i + 3])); }
                    n0 = fmaxf(n0, __shfl_xor_sync(0xffffffffu, n0, 1)); n0 = fmaxf(n0, __shfl_xor_sync(0xffffffffu, n0, 2));
                    n1 = fmaxf(n1, __shfl_xor_sync(0xffffffffu, n1, 1)); n1 = fmaxf(n1, __shfl_xor_sync(0xffffffffu, n1, 2));
                    const float f0 = ex2(m0 - n0), f1 = ex2(m1 - n1);
                    m0 = n0; m1 = n1;
#pragma unroll
                    for (int i = 0; i < 3; i++) { O[4 * i] *= f0; O[4 * i + 1] *= f0; O[4 * i + 2] *= f1; O[4 * i + 3] *= f1; }
#pragma unroll
                    for (int i = 0; i < 8; i++) {
                        P[2 * i] = pack_bf16(ex2(SA[4 * i] - m0), ex2(SA[4 * i + 1] - m0));
                        P[2 * i + 1] = pack_bf16(ex2(SA[4 * i + 2] - m1), ex2(SA[4 * i + 3] - m1));
                    }
                    keep<16>(P); keep<12>(O);
                    WG_FENCE();
                    pv(O, P, P + 8, dv0 + so); WG_COMMIT();
                    WG_WAIT(0);
                    keep<12>(O);
                }
                if (elect && T + 1 < Tend) mbar_arrive(BAR_EMPTYKV + 8 * (T & 7));
            }
        }
        if (elect) mbar_arrive(BAR_EMPTYKV + 8 * ((T - 1) & 7));
        if (wg == 1) TS2(4 + seg);
        if (len == 1) {
            float4* pp = g_part + ((rd - 252) * XS + s0) * 2048 + threadIdx.x;
            pp[0] = make_float4(O[0], O[1], O[2], O[3]); pp[512] = make_float4(O[4], O[5], O[6], O[7]);
            pp[1024] = make_float4(O[8], O[9], O[10], O[11]); pp[1536] = make_float4(m0, m1, 0.f, 0.f);
            pending = &g_pflag[(rd - 252) * 32 + s0]; pstride = 16;
            __syncwarp();
            if (lane == 0) mbar_arrive(BAR_DEP + 8 * (seg & 1));
            continue;
        }
        const int head = rd >> 3, rb = (rd & 7) * 4 + wg, g = lane >> 2;
        const float l0 = __shfl_sync(0xffffffffu, O[8], (lane & ~3) | 1), l1 = __shfl_sync(0xffffffffu, O[10], (lane & ~3) | 1);
        const float r0 = __frcp_rn(l0), r1 = __frcp_rn(l1);
        uint8_t* ob = g_o + (size_t)(rb >> 1) * (9 * 16384) + ((rb & 1) * 8 + warp * 2) * 1024 + g * 16;
#pragma unroll
        for (int i = 0; i < 3; i++) {
            const int c = head * 18 + (i < 2 ? 4 * i + (t & 2) + 8 * (t & 1) : 16);
            uint8_t* op = ob + (c >> 6) * 16384 + ((c >> 3) & 7) * 128 + (c & 7) * 2;
            if (i < 2 || t == 0) {
                *(uint32_t*)op = pack_bf16(O[4 * i] * r0, O[4 * i + 1] * r0);
                *(uint32_t*)(op + 1024) = pack_bf16(O[4 * i + 2] * r1, O[4 * i + 3] * r1);
            }
        }
        pending = &g_oflag[(rd & 7) * 128 + head * 2]; pstride = 64;
        __syncwarp();
        if (lane == 0) mbar_arrive(BAR_DEP + 8 * (seg & 1));
    }
    bar_sync(4 + wg, 128);
    if (elect) st_release(pending + flag_off(wg, pstride), tag);
}

__global__ void __cluster_dims__(2, 1, 1) __launch_bounds__(NTHREADS, 1) fused_kernel(const __grid_constant__ Params p) {
    extern __shared__ __align__(1024) uint8_t smem_raw[];
    if ((uint32_t)__cvta_generic_to_shared(smem_raw) != cl(SB)) asm volatile("trap;");
    const int wg = __shfl_sync(0xffffffffu, threadIdx.x >> 7, 0);
    const int lane = threadIdx.x & 31;
    const bool elect = (threadIdx.x & 127) == 0;
    const bool gemm = blockIdx.x < 128;
    const bool five = cta_j() == 2 || cta_j() == 5;
    if (threadIdx.x >= 32 && threadIdx.x < 41) asm volatile("prefetch.tensormap [%0];" :: "l"(&p.wq4 + (threadIdx.x - 32)) : "memory");
    const int lrow = (blockIdx.x & 1) * 64 + (threadIdx.x >> 3);
    uint32_t v[36];
    if (gemm) {
        const uint4* xr = (const uint4*)(p.xp + (size_t)(cta_m() * 128 + lrow) * DM) + (lane & 7);
#pragma unroll
        for (int i = 0; i < 9; i++) { const uint4 w = __ldg(xr + i * 8); v[4 * i] = w.x; v[4 * i + 1] = w.y; v[4 * i + 2] = w.z; v[4 * i + 3] = w.w; }
        if (threadIdx.x >= 384 && threadIdx.x < 506 && blockIdx.x * 15616 + (threadIdx.x - 384) * 128 < 1728 * DM * 2)
            asm volatile("prefetch.global.L2 [%0];" :: "l"((const uint8_t*)p.wqkvp + blockIdx.x * 15616 + (threadIdx.x - 384) * 128) : "memory");
    }
    if ((threadIdx.x & 31) < NBARS / 16) {
        const int i = (threadIdx.x >> 5) * (NBARS / 16) + (threadIdx.x & 31);
        const uint32_t cnt = (i >= 55 && i < 64) || i == 79 ? 2 : (i >= 38 && i < 46 ? 4 : ((i == 66 || i == 67) && !cta_isG() ? 16 : 1));
        mbar_init(BAR_OFF + 8 * i, cnt);
        asm volatile("fence.mbarrier_init.release.cluster;" ::: "memory");
    }
    if (threadIdx.x >= 40 && threadIdx.x < 43) asm volatile("st.shared.u32 [%0], %1;" :: "r"(cl(BMAX_OFF + 4 * (threadIdx.x - 40))), "r"(0) : "memory");
    __syncthreads();
    asm volatile("barrier.cluster.arrive.relaxed.aligned;" ::: "memory");
    TS(wg);
    if (gemm) {
        const int ks = __shfl_sync(0xffffffffu, threadIdx.x >> 5, 0);
        if (ks < (five ? 7 : 9)) {
            const int st = five ? (ks == 0 ? 6 : ks - 1) : ks;
            if (five && ks > 0 && lane < 3) mbar_arrive(lane == 0 ? BAR_FULLW + 8 * st : BAR_EMPTYW + 8 * st);
            __syncwarp();
            tma3d(B_OFF + st * (five ? 10240 : 8192), five ? &p.wq5 : &p.wq4, ks * 16, (216 * cta_j()) >> 6, BAR_FULLW + 8 * st, five ? 10240 : 8192);
        }
        float f[72], s = 0.f, s2 = 0.f;
#pragma unroll
        for (int i = 0; i < 36; i++) { f[2 * i] = bf_lo(v[i]); f[2 * i + 1] = bf_hi(v[i]); s += f[2 * i]; s2 += f[2 * i + 1]; }
        s += s2;
        s += __shfl_xor_sync(0xffffffffu, s, 1); s += __shfl_xor_sync(0xffffffffu, s, 2); s += __shfl_xor_sync(0xffffffffu, s, 4);
        const float mean = s * (1.0f / DM);
        if (wg == 1) TS(29);
        float q = 0.f, q2 = 0.f;
#pragma unroll
        for (int i = 0; i < 36; i++) { f[2 * i] -= mean; f[2 * i + 1] -= mean; q = fmaf(f[2 * i], f[2 * i], q); q2 = fmaf(f[2 * i + 1], f[2 * i + 1], q2); }
        q += q2;
        q += __shfl_xor_sync(0xffffffffu, q, 1); q += __shfl_xor_sync(0xffffffffu, q, 2); q += __shfl_xor_sync(0xffffffffu, q, 4);
        const float rstd = rsqrtf(q * (1.0f / DM) + 1e-5f);
        const uint32_t dst = cl(A_OFF + lrow * 128 + (((lane & 7) ^ (lrow & 7)) << 4));
#pragma unroll
        for (int i = 0; i < 9; i++)
            asm volatile("st.shared.v4.b32 [%0], {%1,%2,%3,%4};" :: "r"(dst + i * 16384),
                "r"(pack_bf16(f[8 * i] * rstd, f[8 * i + 1] * rstd)), "r"(pack_bf16(f[8 * i + 2] * rstd, f[8 * i + 3] * rstd)),
                "r"(pack_bf16(f[8 * i + 4] * rstd, f[8 * i + 5] * rstd)), "r"(pack_bf16(f[8 * i + 6] * rstd, f[8 * i + 7] * rstd)) : "memory");
        if (wg == 1) TS(31);
        asm volatile("fence.proxy.async.shared::cta;" ::: "memory");
    }
    asm volatile("barrier.cluster.wait.aligned;" ::: "memory");
    __syncthreads();
    if (gemm && threadIdx.x < 32) { send_half(0); send_half(1); }
    TS(28);

    if (wg == 0) {
        asm volatile("setmaxnreg.dec.sync.aligned.u32 24;");
        const int warp = __shfl_sync(0xffffffffu, threadIdx.x >> 5, 0);
        if (warp == 0) {
            if (gemm) {
                int st = five ? 6 : 0; uint32_t ph = 0;
                const int nst = five ? 7 : 9; const uint32_t sb = five ? 10240 : 8192;
#pragma unroll 1
                for (int ks = nst; ks < 36; ks++) {
                    const int i = ks - nst;
                    if ((i % 3) == 0 && i < 21) send_half(2 + i / 3);
                    mbar_wait(BAR_EMPTYW + 8 * st, ph);
                    tma3d(B_OFF + st * sb, five ? &p.wq5 : &p.wq4, ks * 16, (216 * cta_j()) >> 6, BAR_FULLW + 8 * st, sb);
                    if (++st == nst) { st = 0; ph ^= 1; }
                }
                st = 0; ph = 1;
                int fresh = 6;
#pragma unroll 1
                for (int q = 0; q < num_jobs(); q++) {
#pragma unroll 1
                    for (int k = 0; k < DM; k += (q < has_mini() ? (mini_w() == 1 ? 96 : 48) : 32)) {
                        if (fresh) { fresh--; mbar_wait(BAR_EMPTYW + 8 * (five ? (st == 5 ? 6 : st + 1) : (3 * st + 2) >> 1), 1); }
                        else mbar_wait(BAR_EMPTYB + 8 * st, ph);
                        tma3d(B_OFF + st * 12288, q < has_mini() ? (mini_w() == 1 ? &p.w1n : &p.w1m) : &p.w1, k, job_chunk(job_id(q)), BAR_FULLB + 8 * st, 12288);
                        if (++st == 6) { st = 0; ph ^= 1; }
                    }
                }
                if (cta_isG()) {
#pragma unroll 1
                    for (int hk = 0; hk < 162; hk++) {
                        mbar_wait(BAR_EMPTYB + 8 * st, ph);
                        if (hk < 144) tma5d(B_OFF + st * 12288, &p.w2, (hk >> 1) * 32 + (hk & 1) * 4, cta_j() * 3, BAR_FULLB + 8 * st, 12288);
                        else tma3d(B_OFF + st * 12288, &p.wo, (hk - 144) * 32, cta_j() * 3, BAR_FULLB + 8 * st, 12288);
                        if (++st == 6) { st = 0; ph ^= 1; }
                    }
                }
            }
        } else if (warp == 1) {
            if (gemm) {
                const unsigned tag = get_tag();
                bar_sync(10, 288);
                if (lane < 3) atomicMax(&g_bound[(3 * cta_j() + lane) * 16], ((unsigned long long)tag << 32) | lds32(BMAX_OFF + 4 * lane));
                __syncwarp();
                if (lane == 0 || (lane == 1 && (cta_j() == 0 || five))) red_release(&g_qkvcnt[lane * 32], 1);
                __syncwarp();
#pragma unroll 1
                for (int q = 0; q < num_jobs(); q++) {
                    bar_sync(job_bar(q), 160);
                    if (lane < (q < has_mini() ? mini_w() : 1)) st_release(&g_hflag[cta_m() * 32 + job_id(q) + lane], tag);
                    __syncwarp();
                }
            }
        } else if (warp == 3) {
            if (cta_isG()) {
                int sa = 0, dep = 0, next_dep = 0; uint32_t pa = 0;
#pragma unroll 1
                for (int kk = 0; kk < 84; kk++) {
                    if (kk == next_dep) {
                        mbar_wait(BAR_DEP + 8 * dep, 0);
                        dep++;
                        next_dep = kk < 63 ? (kk == 0 ? 30 : (kk == 30 ? 54 : 63)) : (kk == 63 ? 75 : kk + 1);
                    }
                    mbar_wait(BAR_EMPTYA + 8 * sa, pa);
                    if (kk >= 72 && kk < 75) tma2d(A_OFF + sa * 16384, &p.x, (3 * cta_j() + kk - 72) * 64, cta_m() * 128, BAR_FULLA + 8 * sa, 16384);
                    else bulk_load(A_OFF + sa * 16384, kk < 72 ? g_h + (size_t)(cta_m() * 72 + kk) * 16384 : g_o + (size_t)(cta_m() * 9 + (kk - 75)) * 16384, 16384, BAR_FULLA + 8 * sa, 16384);
                    if (++sa == 9) { sa = 0; pa ^= 1; }
                }
            } else {
                const unsigned tag = get_tag();
                task_table(lane);
                if (gemm) mbar_wait(BAR_WDONE, 0);
#pragma unroll 1
                for (int pass = gemm; pass < 2; pass++) {
                    flag_wait(&g_qkvcnt[pass ? 0 : 32], tag * (pass ? 128 : 48));
                    __syncwarp();
                    const float bn = lane < 24 ? __uint_as_float((uint32_t)ld_tagged(&g_bound[lane * 16])) * 1.02f : 0.f;
                    asm volatile("fence.proxy.async.global;" ::: "memory");
                    const float bk = __shfl_sync(0xffffffffu, bn, (lane & 7) + 8), bv = __shfl_sync(0xffffffffu, bn, (lane & 7) + 16);
                    const uint32_t fastmask = __ballot_sync(0xffffffffu, __fsqrt_rn(bn * bk) + 0.5f * __log2f(fmaxf(bv, 1.0f)) <= GUARD);
                    asm volatile("st.shared.u32 [%0], %1;" :: "r"(cl(FAST_OFF)), "r"(fastmask) : "memory");
                    __syncwarp();
                    if (pass == gemm) {
#pragma unroll 1
                        for (int s = 0; s < 8; s++) {
                            if (gemm) mbar_wait(BAR_EMPTYA + 8 * (s == 0 ? 7 : 8), 0);
                            kv_load(s);
                        }
                    }
                }
            }
        } else {
            if (gemm) l2_prefetch((const uint8_t*)p.w1p + blockIdx.x * 41472, 41472, 300);
            if (cta_isG()) {
                const unsigned tag = get_tag();
                mbar_wait(BAR_WDONE, 0);
#pragma unroll 1
                for (int d = 0; d < 4; d++) {
                    if (lane < (d == 0 ? 14 : 19 + 3 * d)) flag_wait(&g_hflag[cta_m() * 32 + lane], tag);
                    __syncwarp();
                    fence_async();
                    if (lane == 0) mbar_arrive(BAR_DEP + 8 * d);
                }
                int d = 0, n = 0;
                const unsigned* f0 = &g_oflag[cta_m() * 64 + lane * 2];
#pragma unroll 1
                while (d < 9) {
                    unsigned a, b;
                    asm volatile("ld.acquire.gpu.global.v2.u32 {%0, %1}, [%2];" : "=r"(a), "=r"(b) : "l"(f0) : "memory");
                    const uint32_t miss = ~__ballot_sync(0xffffffffu, a == tag && b == tag);
                    const int ready = miss ? ((__ffs(miss) - 1) * 18) >> 6 : 9;
                    if (ready > d) {
                        asm volatile("fence.proxy.async.global;" ::: "memory");
                        if (lane >= d && lane < ready) mbar_arrive(BAR_DEP + 8 * (4 + lane));
                        d = ready;
                    } else asm volatile("{\n.reg .pred q;\nnanosleep.u32 %1;\nsetp.gt.u32 q, %0, 4000000;\n@q trap;\n}" :: "r"(++n), "r"(d < 5 ? 500 : 20));
                }
            }
        }
        if (cta_isG()) {
            bar_sync(4, 128);
            if (elect) red_relaxed(&g_done, 1);
            return;
        }
        bar_sync(2, 256);
        asm volatile("setmaxnreg.inc.sync.aligned.u32 128;");
    } else if (wg == 3) {
        asm volatile("setmaxnreg.dec.sync.aligned.u32 24;");
        if (gemm) {
            const int tid = threadIdx.x & 127;
#pragma unroll 2
            for (int w = tid; w < 1024; w += 128) {
                uint32_t bw, bdst;
                if (w < 768) {
                    const int c = w >> 8, r = (w >> 5) & 7, k = w & 31;
                    bw = (r < num_jobs() && (r >= has_mini() || c < mini_w())) ? __ldg((const uint32_t*)p.b1p + (job_chunk(job_id(r)) + c) * 32 + k) : 0u;
                    if (r == 5 && cta_isG()) bw = __ldg((const uint32_t*)p.b2p + (3 * cta_j() + c) * 32 + k);
                    bdst = BIAS_OFF + c * 1024 + r * 128 + (((k >> 2) ^ r) << 4) + (k & 3) * 4;
                } else {
                    const int u = w - 768, q = u >> 5, k = u & 3;
                    bw = (q < 6 && k == (q >> 1)) ? (q == 5 ? 0x40000000u : ((q & 1) ? 0x3f800000u : 0x00003f80u)) : 0u;
                    bdst = ONE_OFF + u * 4;
                }
                asm volatile("st.shared.u32 [%0], %1;" :: "r"(cl(bdst)), "r"(bw) : "memory");
            }
            asm volatile("fence.proxy.async.shared::cta;" ::: "memory");
            bar_sync(7, 128);
            if (elect) mbar_arrive(BAR_INFO);
        }
        if (cta_isG()) {
            if ((threadIdx.x >> 5) == 12) {
                mbar_wait(BAR_EMPTYA, 0);
#pragma unroll 1
                for (int line = (cta_m() * 3 + cta_j()) * 32 + lane; line < 41472 + 5184; line += 1536) {
                    asm volatile("prefetch.global.L2 [%0];" :: "l"(line < 41472 ? (const uint8_t*)p.w2p + line * 128 : (const uint8_t*)p.wop + (line - 41472) * 128) : "memory");
                    asm volatile("nanosleep.u32 %0;" :: "n"(PF2NS));
                }
                __syncwarp();
            }
            if (elect) red_relaxed(&g_done, 1);
            return;
        }
        bar_sync(1, 256);
        asm volatile("setmaxnreg.inc.sync.aligned.u32 128;");
    } else {
        const int warp = __shfl_sync(0xffffffffu, (threadIdx.x >> 5) & 3, 0), g = lane >> 2, t = lane & 3;
        asm volatile("setmaxnreg.inc.sync.aligned.u32 232;");
        if (gemm) {
            uint32_t vv[54];
            switch (cta_j()) {
                case 0: qkv_mainloop<0>(vv, wg, elect); break;
                case 1: qkv_mainloop<1>(vv, wg, elect); break;
                case 2: qkv_mainloop<2>(vv, wg, elect); break;
                case 3: qkv_mainloop<3>(vv, wg, elect); break;
                case 4: qkv_mainloop<4>(vv, wg, elect); break;
                case 5: qkv_mainloop<5>(vv, wg, elect); break;
                case 6: qkv_mainloop<6>(vv, wg, elect); break;
                default: qkv_mainloop<7>(vv, wg, elect); break;
            }
            if (wg == 1) TS(26);
            float acc0[96], acc1[96];
            kill<96>(acc0); kill<96>(acc1);
            mbar_wait(BAR_INFO, 0);
            mbar_wait(BAR_WDONE, 0);
            keep<54>(vv);
            if (wg == 1 && has_mini()) { if (mini_w() == 1) mini_mainloop<1>(acc0, acc1, elect); else mini_mainloop<2>(acc0, acc1, elect); TS(17); }
            keep<54>(vv);
            epilogue_qkv(vv, cta_m() * 16 + (wg - 1) * 8 + warp * 2, g, t, wg);
            if (wg == 1 && !has_mini()) bar_arrive(14, 256);
            TS(wg == 1 ? 27 : 30);
            bar_arrive(10, 288);
#pragma unroll 1
            for (int q = wg - 1; q < num_jobs() + cta_isG(); q += 2) {
                const bool g2 = q == num_jobs();
                const uint32_t xa = A_OFF + (warp * 16 + (lane & 15)) * 128 + (((lane >> 4) ^ (lane & 7)) << 4);
                if (g2) TS2(9);
                if (q >= has_mini()) job_mainloop(acc0, acc1, q, g2, xa, elect);
                if (g2) {
                    TS2(12);
#pragma unroll
                    for (int c = 0; c < 3; c++) {
#pragma unroll
                        for (int i2 = 4 * c; i2 < 4 * c + 4; i2++) {
#pragma unroll
                            for (int mh = 0; mh < 2; mh++) {
                                const float* a = (mh ? acc1 : acc0) + 8 * i2;
                                asm volatile("stmatrix.sync.aligned.m8n8.x4.shared.b16 [%0], {%1,%2,%3,%4};"
                                    :: "r"(cl((xa ^ ((i2 & 3) << 5)) + (3 + c) * 16384 + mh * 8192)),
                                       "r"(pack_bf16(a[0], a[1])), "r"(pack_bf16(a[2], a[3])), "r"(pack_bf16(a[4], a[5])), "r"(pack_bf16(a[6], a[7])) : "memory");
                            }
                        }
                        asm volatile("fence.proxy.async.shared::cta;" ::: "memory");
                        bar_sync(4 + wg, 128);
                        if (elect) asm volatile("cp.async.bulk.tensor.2d.global.shared::cta.bulk_group [%0, {%1, %2}], [%3];"
                                        :: "l"(&p.outm), "r"(cta_j() * 192 + c * 64), "r"(cta_m() * 128), "r"(cl(A_OFF + (3 + c) * 16384)) : "memory");
                    }
                    if (elect) asm volatile("cp.async.bulk.commit_group;\ncp.async.bulk.wait_group.read 0;" ::: "memory");
                    TS2(14);
                    break;
                }
                if (q >= has_mini()) TS(17 + (q < 4 ? q : 4));
                job_epilogue(acc0, acc1, q, warp, g, t);
                TS(22 + (q < 3 ? q : 3));
            }
        }
        if (cta_isG()) {
            bar_sync(4 + wg, 128);
            if (elect) red_relaxed(&g_done, 1);
            return;
        }
        asm volatile("setmaxnreg.dec.sync.aligned.u32 128;");
        bar_arrive(has_mini() ? 3 - wg : wg, 256);
    }
    __syncwarp();
    TS2(8 + wg);
    attention(wg, get_tag());
    TS2(12 + wg);
    bar_sync(4 + wg, 128);
    if (elect) red_relaxed(&g_done, 1);
}

typedef CUresult (*EncFn)(CUtensorMap*, CUtensorMapDataType, cuuint32_t, void*, const cuuint64_t*, const cuuint64_t*, const cuuint32_t*,
                          const cuuint32_t*, CUtensorMapInterleave, CUtensorMapSwizzle, CUtensorMapL2promotion, CUtensorMapFloatOOBfill);

void make_map(EncFn enc, CUtensorMap* m, const void* ptr, int rank, const cuuint64_t* dims, const cuuint64_t* strides, const cuuint32_t* box) {
    cuuint32_t es[5] = {1, 1, 1, 1, 1};
    enc(m, CU_TENSOR_MAP_DATA_TYPE_BFLOAT16, rank, const_cast<void*>(ptr), dims, strides, box, es, CU_TENSOR_MAP_INTERLEAVE_NONE,
        CU_TENSOR_MAP_SWIZZLE_128B, L2PROMO, CU_TENSOR_MAP_FLOAT_OOB_FILL_NONE);
}
void make_act_map(EncFn enc, CUtensorMap* m, const void* ptr, int cols) {
    cuuint64_t d[2] = {(cuuint64_t)cols, SEQ}, s[1] = {(cuuint64_t)cols * 2}; cuuint32_t b[2] = {64, 128};
    make_map(enc, m, ptr, 2, d, s, b);
}

}

extern "C" void kernel_launch(void* const* d_in, const int* in_sizes, int n_in, void* d_out, int out_size) {
    static Params prm;
    static bool ready = false;
    static const void* key[9];
    bool same = ready && key[8] == d_out;
    for (int i = 0; i < 8 && same; i++) same = key[i] == d_in[i];
    if (!same) {
        EncFn enc = nullptr; cudaDriverEntryPointQueryResult qr;
        cudaGetDriverEntryPoint("cuTensorMapEncodeTiled", (void**)&enc, cudaEnableDefault, &qr);
        make_act_map(enc, &prm.outm, d_out, DM);
        make_act_map(enc, &prm.x, d_in[0], DM);
        {
            cuuint64_t d[3] = {64, DM, 27}, s[2] = {1728 * 2, 128}; cuuint32_t b4[3] = {64, 16, 4}, b5[3] = {64, 16, 5};
            make_map(enc, &prm.wq4, d_in[1], 3, d, s, b4);
            make_map(enc, &prm.wq5, d_in[1], 3, d, s, b5);
        }
        {
            cuuint64_t d[3] = {64, DM, FF / 64}, s[2] = {FF * 2, 128}; cuuint32_t b[3] = {64, 32, 3};
            make_map(enc, &prm.w1, d_in[4], 3, d, s, b);
            cuuint32_t bn[3] = {64, 96, 1};
            make_map(enc, &prm.w1n, d_in[4], 3, d, s, bn);
            cuuint32_t bm[3] = {64, 48, 2};
            make_map(enc, &prm.w1m, d_in[4], 3, d, s, bm);
        }
        {
            cuuint64_t d[3] = {64, DM, DM / 64}, s[2] = {DM * 2, 128}; cuuint32_t b[3] = {64, 32, 3};
            make_map(enc, &prm.wo, d_in[2], 3, d, s, b);
        }
        {
            cuuint64_t d[5] = {64, 2, 4, 2280, DM / 64}, s[4] = {DM * 2, 16 * DM * 2, 2 * DM * 2, 128}; cuuint32_t b[5] = {64, 2, 4, 4, 3};
            make_map(enc, &prm.w2, d_in[6], 5, d, s, b);
        }
        prm.xp = (const __nv_bfloat16*)d_in[0]; prm.wqkvp = (const __nv_bfloat16*)d_in[1]; prm.w1p = (const __nv_bfloat16*)d_in[4];
        prm.b1p = (const __nv_bfloat16*)d_in[5]; prm.b2p = (const __nv_bfloat16*)d_in[7]; prm.out = (__nv_bfloat16*)d_out;
        prm.w2p = (const __nv_bfloat16*)d_in[6]; prm.wop = (const __nv_bfloat16*)d_in[2];
        cudaFuncSetAttribute(fused_kernel, cudaFuncAttributeMaxDynamicSharedMemorySize, SMEM_BYTES);
        for (int i = 0; i < 8; i++) key[i] = d_in[i];
        key[8] = d_out; ready = true;
    }
    fused_kernel<<<NCTA, NTHREADS, SMEM_BYTES, cudaStreamPerThread>>>(prm);
}
```
